```python
import torch

def _softmax(x, axis=-1):
    return torch.softmax(x, dim=axis)
def _gelu(x):
    return torch.nn.functional.gelu(x, approximate="tanh")
def _silu(x):
    return torch.nn.functional.silu(x)
def _sigmoid(x):
    return torch.sigmoid(x)
def _layernorm(x, axis=-1, eps=1e-5):
    m = x.mean(dim=axis, keepdim=True)
    v = x.var(dim=axis, keepdim=True, unbiased=False)
    return (x - m) / torch.sqrt(v + eps)
def _scatter_add(tgt, idx, src, axis=0):
    return tgt.clone().index_add_(axis, idx, src)
def _segment_sum(src, seg, n):
    out = torch.zeros((n,) + src.shape[1:], dtype=src.dtype)
    return out.index_add_(0, seg, src)
def _pad(x, pw):
    flat = tuple(v for pair in reversed(pw) for v in pair)
    return torch.nn.functional.pad(x, flat)

kernel_name = 'parallel_sum__gqa_block_cached__swiglu_ffn__decode'

def setup_inputs():

    _w = (lambda a: (lambda t: t.to(torch.bfloat16) if t.is_floating_point() else t)(torch.as_tensor(a)))
    def _A_setup():
        B, Sq, D = 1, 1, 576
        Hq, Hkv, Sk, Dh = 32, 16, 16384, 128
        assert Hq % Hkv == 0, (Hq, Hkv)
        return {
            "x": _w((lambda *s: torch.randn(*s, dtype=torch.bfloat16) * 0.05)(B, Sq, D)),
            "k_cache": _w((lambda *s: torch.randn(*s, dtype=torch.bfloat16) * 3.2)(B, Hkv, Sk, Dh)),
            "v_cache": _w((lambda *s: torch.randn(*s, dtype=torch.bfloat16) * 1.6)(B, Hkv, Sk, Dh)),
            "wq": _w((lambda *s: torch.randn(*s, dtype=torch.bfloat16) * 3.2)(D, Hq * Dh) * (D ** -0.5)),
            "wo": _w((lambda *s: torch.randn(*s, dtype=torch.bfloat16) * 1.6)(Hq * Dh, D) * ((Hq * Dh) ** -0.5)),
        }
    _A_in = _A_setup()

    def _B_setup():
        B, S, D, F = 1, 1, 576, 4608
        return {
            "x": _w((lambda *s: torch.randn(*s, dtype=torch.bfloat16) * 0.05)(B, S, D)),
            "w_gate": _w((lambda *s: torch.randn(*s, dtype=torch.bfloat16) * 0.05)(D, F)),
            "w_up": _w((lambda *s: torch.randn(*s, dtype=torch.bfloat16) * 0.05)(D, F)),
            "w_down": _w((lambda *s: torch.randn(*s, dtype=torch.bfloat16) * 0.05)(F, D)),
        }
    _B_in = _B_setup()

    return {
        "A_x": _A_in["x"],
        "A_k_cache": _A_in["k_cache"],
        "A_v_cache": _A_in["v_cache"],
        "A_wq": _A_in["wq"],
        "A_wo": _A_in["wo"],
        "B_x": _B_in["x"],
        "B_w_gate": _B_in["w_gate"],
        "B_w_up": _B_in["w_up"],
        "B_w_down": _B_in["w_down"],
    }

def reference(A_x, A_k_cache, A_v_cache, A_wq, A_wo, B_x, B_w_gate, B_w_up, B_w_down):
    def _A_ref(x, k_cache, v_cache, wq, wo):
        B, Sq, D = x.shape
        Hq, Dh = 32, 128
        Hkv = k_cache.shape[1]
        rep = Hq // Hkv
        q = (lambda x, *d: x.permute(*d))((x @ wq).reshape(B, Sq, Hq, Dh), 0, 2, 1, 3)
        k = (lambda x, n, axis: torch.repeat_interleave(x, n, dim=axis))(k_cache, rep, axis=1)
        v = (lambda x, n, axis: torch.repeat_interleave(x, n, dim=axis))(v_cache, rep, axis=1)
        scores = torch.einsum("bhqd,bhkd->bhqk", q, k) * (Dh ** -0.5)
        p = _softmax(scores, axis=-1)
        o = torch.einsum("bhqk,bhkd->bhqd", p, v)
        return (lambda x, *d: x.permute(*d))(o, 0, 2, 1, 3).reshape(B, Sq, Hq * Dh) @ wo

    def _B_ref(x, w_gate, w_up, w_down):
        g = _silu(x @ w_gate)
        u = x @ w_up
        return (g * u) @ w_down

    x = A_x
    xn = _layernorm(x, axis=-1)
    return x + _A_ref(xn, A_k_cache, A_v_cache, A_wq, A_wo) + _B_ref(xn, B_w_gate, B_w_up, B_w_down)
```

```cpp
#include <cuda_runtime.h>
#include <cuda.h>
#include <cuda_bf16.h>
#include <stdint.h>

namespace {

constexpr int DM = 576, HKV = 16, SK = 16384, FF = 4608, QW = 4096;
constexpr int CHUNK = 128;
constexpr int CH_PER_HEAD = SK / CHUNK;
constexpr int NCHUNK = HKV * CH_PER_HEAD;
constexpr int NW1 = (QW + 2 * FF) / 32;
constexpr int W1_BYTES = DM * 64;
constexpr int KV_BYTES = CHUNK * 256;
constexpr int ROW_BYTES = DM * 2;
constexpr int WD_PIECE = 34;
constexpr int STAGE_BYTES = 39936;
constexpr int NST = 5;
constexpr int REC = 136;
constexpr int MAXG = 144;
constexpr int MAXH = 160;
constexpr int NCONS = 256;
constexpr int NTHREADS = 320;
constexpr int SPIN_LIMIT = 1 << 22;

constexpr int OFF_RING = 0;
constexpr int OFF_Q = OFF_RING + NST * STAGE_BYTES;
constexpr int OFF_P = OFF_Q + 8192;
constexpr int OFF_RED = OFF_P + 512;
constexpr int OFF_WMAX = OFF_RED + 2048;
constexpr int OFF_WSUM = OFF_WMAX + 64;
constexpr int OFF_H = OFF_WSUM + 64;
constexpr int OFF_CMB = OFF_H + MAXH * 4;
constexpr int OFF_ITEM = OFF_CMB + 1152;
constexpr int OFF_BAR = OFF_ITEM + 32;
constexpr int SMEM_USED = OFF_BAR + (2 * NST + 1) * 8;
constexpr int SMEM_BYTES = SMEM_USED + 1024;

struct Params {
    const __nv_bfloat16* x;
    const __nv_bfloat16* wo;
    const __nv_bfloat16* wd;
    __nv_bfloat16* out;
    unsigned short wd_start[MAXG + 1];
};

__device__ float g_part[NCHUNK * 2 * REC];
__device__ float g_y1[QW + 2 * FF];
__device__ float g_fin[MAXG * DM];
__device__ unsigned g_epoch;
__device__ unsigned g_ctr;
#define TRACE(i)
#define TRACEV(i, v)

__device__ __forceinline__ uint32_t smem_u32(const void* p) { return (uint32_t)__cvta_generic_to_shared(p); }
__device__ __forceinline__ void mbar_init(uint32_t bar, int cnt) {
    asm volatile("mbarrier.init.shared::cta.b64 [%0], %1;" ::"r"(bar), "r"(cnt));
}
__device__ __forceinline__ void mbar_expect_tx(uint32_t bar, uint32_t bytes) {
    asm volatile("mbarrier.arrive.expect_tx.shared::cta.b64 _, [%0], %1;" ::"r"(bar), "r"(bytes) : "memory");
}
__device__ __forceinline__ void mbar_arrive(uint32_t bar) {
    asm volatile("mbarrier.arrive.shared::cta.b64 _, [%0];" ::"r"(bar) : "memory");
}
__device__ __forceinline__ void mbar_wait(uint32_t bar, uint32_t parity) {
    uint32_t ok;
    int it = 0;
    do {
        asm volatile(
            "{\n.reg .pred p;\n"
            "mbarrier.try_wait.parity.shared::cta.b64 p, [%1], %2;\n"
            "selp.u32 %0, 1, 0, p;\n}"
            : "=r"(ok) : "r"(bar), "r"(parity) : "memory");
    } while (!ok && ++it < SPIN_LIMIT);
}
__device__ __forceinline__ void bulk_g2s(uint32_t dst, const void* src, uint32_t bytes, uint32_t bar, uint64_t pol) {
    asm volatile(
        "cp.async.bulk.shared::cluster.global.mbarrier::complete_tx::bytes.L2::cache_hint [%0], [%1], %2, [%3], %4;"
        ::"r"(dst), "l"(src), "r"(bytes), "r"(bar), "l"(pol) : "memory");
}
__device__ __forceinline__ void tma3d(uint32_t dst, const CUtensorMap* tm, int c0, int c1, int c2, uint32_t bar) {
    asm volatile(
        "cp.async.bulk.tensor.3d.shared::cluster.global.mbarrier::complete_tx::bytes [%0], [%1, {%3,%4,%5}], [%2];"
        ::"r"(dst), "l"(tm), "r"(bar), "r"(c0), "r"(c1), "r"(c2) : "memory");
}
__device__ __forceinline__ void tma3d_hint(uint32_t dst, const CUtensorMap* tm, int c0, int c1, int c2, uint32_t bar, uint64_t pol) {
    asm volatile(
        "cp.async.bulk.tensor.3d.shared::cluster.global.mbarrier::complete_tx::bytes.L2::cache_hint [%0], [%1, {%3,%4,%5}], [%2], %6;"
        ::"r"(dst), "l"(tm), "r"(bar), "r"(c0), "r"(c1), "r"(c2), "l"(pol) : "memory");
}
__device__ __forceinline__ void cons_sync() { asm volatile("bar.sync 1, 256;" ::: "memory"); }

__device__ __forceinline__ uint4 lds128(uint32_t a) {
    uint4 v;
    asm volatile("ld.shared.v4.u32 {%0,%1,%2,%3}, [%4];" : "=r"(v.x), "=r"(v.y), "=r"(v.z), "=r"(v.w) : "r"(a));
    return v;
}
__device__ __forceinline__ void ldsm4(uint32_t* r, uint32_t a) {
    asm volatile("ldmatrix.sync.aligned.m8n8.x4.shared.b16 {%0,%1,%2,%3}, [%4];"
                 : "=r"(r[0]), "=r"(r[1]), "=r"(r[2]), "=r"(r[3]) : "r"(a));
}
__device__ __forceinline__ void ldsm4t(uint32_t* r, uint32_t a) {
    asm volatile("ldmatrix.sync.aligned.m8n8.x4.trans.shared.b16 {%0,%1,%2,%3}, [%4];"
                 : "=r"(r[0]), "=r"(r[1]), "=r"(r[2]), "=r"(r[3]) : "r"(a));
}
__device__ __forceinline__ void mma16816(float* c, const uint32_t* a, uint32_t b0, uint32_t b1) {
    asm volatile(
        "mma.sync.aligned.m16n8k16.row.col.f32.bf16.bf16.f32 {%0,%1,%2,%3}, {%4,%5,%6,%7}, {%8,%9}, {%0,%1,%2,%3};"
        : "+f"(c[0]), "+f"(c[1]), "+f"(c[2]), "+f"(c[3])
        : "r"(a[0]), "r"(a[1]), "r"(a[2]), "r"(a[3]), "r"(b0), "r"(b1));
}
__device__ __forceinline__ uint4 ld_rlx4(const void* p) {
    uint4 v;
    asm volatile("ld.relaxed.gpu.global.v4.u32 {%0,%1,%2,%3}, [%4];"
                 : "=r"(v.x), "=r"(v.y), "=r"(v.z), "=r"(v.w) : "l"(p) : "memory");
    return v;
}
__device__ __forceinline__ uint2 ld_rlx2(const void* p) {
    uint2 v;
    asm volatile("ld.relaxed.gpu.global.v2.u32 {%0,%1}, [%2];" : "=r"(v.x), "=r"(v.y) : "l"(p) : "memory");
    return v;
}
__device__ __forceinline__ uint32_t ld_rlx1(const void* p) {
    uint32_t v;
    asm volatile("ld.relaxed.gpu.global.u32 %0, [%1];" : "=r"(v) : "l"(p) : "memory");
    return v;
}
__device__ __forceinline__ void st_rlx1(void* p, uint32_t v) {
    asm volatile("st.relaxed.gpu.global.u32 [%0], %1;" ::"l"(p), "r"(v) : "memory");
}
__device__ __forceinline__ void st_rlx4(void* p, uint4 v) {
    asm volatile("st.relaxed.gpu.global.v4.u32 [%0], {%1,%2,%3,%4};" ::"l"(p), "r"(v.x), "r"(v.y), "r"(v.z), "r"(v.w) : "memory");
}
__device__ __forceinline__ uint32_t tagf(float v, uint32_t tag) { return (__float_as_uint(v) & ~1u) | tag; }
__device__ __forceinline__ float untag(uint32_t w) { return __uint_as_float(w & ~1u); }
__device__ __forceinline__ bool ok4(uint4 v, uint32_t tag) {
    return ((((v.x ^ tag) | (v.y ^ tag)) | ((v.z ^ tag) | (v.w ^ tag))) & 1u) == 0u;
}
__device__ __forceinline__ bool ok2(uint2 v, uint32_t tag) { return (((v.x ^ tag) | (v.y ^ tag)) & 1u) == 0u; }
__device__ __forceinline__ float bf16r(float v) { return __bfloat162float(__float2bfloat16_rn(v)); }
__device__ __forceinline__ float blo(uint32_t w) { return __uint_as_float(w << 16); }
__device__ __forceinline__ float bhi(uint32_t w) { return __uint_as_float(w & 0xffff0000u); }
__device__ __forceinline__ float ex2(float v) { float r; asm("ex2.approx.ftz.f32 %0, %1;" : "=f"(r) : "f"(v)); return r; }
__device__ __forceinline__ void fma8(float* acc, float s, uint4 w) {
    acc[0] = fmaf(s, blo(w.x), acc[0]); acc[1] = fmaf(s, bhi(w.x), acc[1]);
    acc[2] = fmaf(s, blo(w.y), acc[2]); acc[3] = fmaf(s, bhi(w.y), acc[3]);
    acc[4] = fmaf(s, blo(w.z), acc[4]); acc[5] = fmaf(s, bhi(w.z), acc[5]);
    acc[6] = fmaf(s, blo(w.w), acc[6]); acc[7] = fmaf(s, bhi(w.w), acc[7]);
}
__device__ __forceinline__ float sum8(uint4 w) {
    return ((blo(w.x) + bhi(w.x)) + (blo(w.y) + bhi(w.y))) + ((blo(w.z) + bhi(w.z)) + (blo(w.w) + bhi(w.w)));
}
__device__ __forceinline__ float sq8(uint4 w, float m) {
    float a, s = 0.f;
    a = blo(w.x) - m; s = fmaf(a, a, s); a = bhi(w.x) - m; s = fmaf(a, a, s);
    a = blo(w.y) - m; s = fmaf(a, a, s); a = bhi(w.y) - m; s = fmaf(a, a, s);
    a = blo(w.z) - m; s = fmaf(a, a, s); a = bhi(w.z) - m; s = fmaf(a, a, s);
    a = blo(w.w) - m; s = fmaf(a, a, s); a = bhi(w.w) - m; s = fmaf(a, a, s);
    return s;
}

constexpr float LOG2E = 1.4426950408889634f;

__global__ void __launch_bounds__(NTHREADS, 1)
fused_decode_kernel(const __grid_constant__ CUtensorMap tm_k, const __grid_constant__ CUtensorMap tm_v,
                    const __grid_constant__ CUtensorMap tm_wq, const __grid_constant__ CUtensorMap tm_wg,
                    const __grid_constant__ CUtensorMap tm_wu, const __grid_constant__ Params prm) {
    extern __shared__ uint8_t smem_raw[];
    const uint32_t sbase = (smem_u32(smem_raw) + 1023u) & ~1023u;
    uint8_t* sptr = smem_raw + (sbase - smem_u32(smem_raw));
    const int tid = threadIdx.x, warp = tid >> 5, lane = tid & 31;
    const int b = blockIdx.x, G = gridDim.x;
    const uint32_t bar_full = sbase + OFF_BAR, bar_empty = bar_full + NST * 8, bar_h = bar_full + 2 * NST * 8;
    volatile int* s_item = reinterpret_cast<volatile int*>(sptr + OFF_ITEM);
    TRACE(0);

    if (tid == NCONS) {
        for (int i = 0; i < NST; i++) { mbar_init(bar_full + i * 8, 1); mbar_init(bar_empty + i * 8, 8); }
        mbar_init(bar_h, 1);
        asm volatile("fence.mbarrier_init.release.cluster;" ::: "memory");
    }
    __syncthreads();

    const int wd0 = prm.wd_start[b], wd1 = prm.wd_start[b + 1];

    if (warp == 8) {
        if (lane == 0) {
            uint64_t pol;
            asm volatile("createpolicy.fractional.L2::evict_first.b64 %0, 1.0;" : "=l"(pol));
            int s = 0; uint32_t ph = 1;
            for (int t = b; t < NW1; t += G) {
                mbar_wait(bar_empty + s * 8, ph);
                mbar_expect_tx(bar_full + s * 8, W1_BYTES);
                const CUtensorMap* tm = t < 128 ? &tm_wq : (t < 272 ? &tm_wg : &tm_wu);
                const int col = (t < 128 ? t : (t < 272 ? t - 128 : t - 272)) * 32;
                tma3d(sbase + s * STAGE_BYTES, tm, col, 0, 0, bar_full + s * 8);
                if (++s == NST) { s = 0; ph ^= 1; }
            }
            int c = b;
            while (c < NCHUNK) {
                mbar_wait(bar_empty + s * 8, ph);
                s_item[s] = c;
                mbar_expect_tx(bar_full + s * 8, KV_BYTES);
                tma3d_hint(sbase + s * STAGE_BYTES, &tm_k, 0, c * CHUNK, 0, bar_full + s * 8, pol);
                if (++s == NST) { s = 0; ph ^= 1; }
                const int nxt = G + (int)atomicInc(&g_ctr, NCHUNK - 1);
                mbar_wait(bar_empty + s * 8, ph);
                mbar_expect_tx(bar_full + s * 8, KV_BYTES);
                tma3d_hint(sbase + s * STAGE_BYTES, &tm_v, 0, c * CHUNK, 0, bar_full + s * 8, pol);
                if (++s == NST) { s = 0; ph ^= 1; }
                c = nxt;
            }
            bool first = true;
            for (int r = wd0; r < wd1 || first; r += WD_PIECE) {
                const int n = min(WD_PIECE, wd1 - r);
                mbar_wait(bar_empty + s * 8, ph);
                s_item[s] = -1;
                if (n > 0) {
                    mbar_expect_tx(bar_full + s * 8, n * ROW_BYTES);
                    bulk_g2s(sbase + s * STAGE_BYTES, prm.wd + (size_t)r * DM, n * ROW_BYTES, bar_full + s * 8, pol);
                } else {
                    mbar_arrive(bar_full + s * 8);
                }
                if (++s == NST) { s = 0; ph ^= 1; }
                first = false;
            }
            for (int t = b; t < 128; t += G) {
                mbar_wait(bar_empty + s * 8, ph);
                mbar_expect_tx(bar_full + s * 8, 32 * ROW_BYTES);
                bulk_g2s(sbase + s * STAGE_BYTES, prm.wo + (size_t)t * 32 * DM, 32 * ROW_BYTES, bar_full + s * 8, pol);
                if (++s == NST) { s = 0; ph ^= 1; }
            }
        }
        return;
    }

    const uint32_t epoch = ld_rlx1(&g_epoch);
    const uint32_t tag = (epoch + 1u) & 1u;

    if (warp == 9) {
        float* h_s = reinterpret_cast<float*>(sptr + OFF_H);
        for (int r = wd0 + lane; r < wd1; r += 32) {
            uint32_t gw, uw;
            int it = 0;
            while (true) {
                gw = ld_rlx1(&g_y1[QW + r]);
                uw = ld_rlx1(&g_y1[QW + FF + r]);
                if (((((gw ^ tag) | (uw ^ tag)) & 1u) == 0u) || ++it >= SPIN_LIMIT) break;
                __nanosleep(500);
            }
            const float gv = untag(gw), uv = untag(uw);
            const float sg = bf16r(gv / (1.f + __expf(-gv)));
            h_s[r - wd0] = bf16r(sg * uv);
        }
        __syncwarp();
        if (lane == 0) mbar_arrive(bar_h);
        return;
    }

    const int g = lane >> 2, j = lane & 3;
    float xr[9];
    {
        const uint4* x4 = reinterpret_cast<const uint4*>(prm.x);
        const uint4 xa = __ldg(x4 + lane), xb = __ldg(x4 + 32 + lane);
        uint4 xc = make_uint4(0, 0, 0, 0);
        if (lane < 8) xc = __ldg(x4 + 64 + lane);
#pragma unroll
        for (int p = 0; p < 9; p++) xr[p] = __bfloat162float(prm.x[p * 64 + warp * 8 + g]);
        float s = sum8(xa) + sum8(xb) + sum8(xc);
#pragma unroll
        for (int o = 16; o; o >>= 1) s += __shfl_xor_sync(~0u, s, o);
        const float mean = s * (1.f / DM);
        float v = sq8(xa, mean) + sq8(xb, mean) + (lane < 8 ? sq8(xc, mean) : 0.f);
#pragma unroll
        for (int o = 16; o; o >>= 1) v += __shfl_xor_sync(~0u, v, o);
        const float mb = bf16r(mean);
        const float sd = bf16r(sqrtf(bf16r(bf16r(v * (1.f / DM)) + 1e-5f)));
#pragma unroll
        for (int p = 0; p < 9; p++) xr[p] = bf16r(bf16r(xr[p] - mb) / sd);
    }
    TRACE(1);

    int s = 0; uint32_t ph = 0;
    {
        float* red = reinterpret_cast<float*>(sptr + OFF_RED);
        int i = 0;
        for (int t = b; t < NW1; t += G, i++) {
            mbar_wait(bar_full + s * 8, ph);
            if (i == 0) TRACE(2);
            const uint32_t a = sbase + s * STAGE_BYTES + warp * 512 + lane * 16;
            float acc[8];
#pragma unroll
            for (int k = 0; k < 8; k++) acc[k] = 0.f;
#pragma unroll
            for (int p = 0; p < 9; p++) fma8(acc, xr[p], lds128(a + p * 4096));
            __syncwarp();
            if (lane == 0) mbar_arrive(bar_empty + s * 8);
            if (++s == NST) { s = 0; ph ^= 1; }
            const bool b4 = lane & 16, b3 = lane & 8, b2 = lane & 4;
            float r4[4], r2[2];
#pragma unroll
            for (int k = 0; k < 4; k++) {
                const float keep = b4 ? acc[k + 4] : acc[k], send = b4 ? acc[k] : acc[k + 4];
                r4[k] = keep + __shfl_xor_sync(~0u, send, 16);
            }
#pragma unroll
            for (int k = 0; k < 2; k++) {
                const float keep = b3 ? r4[k + 2] : r4[k], send = b3 ? r4[k] : r4[k + 2];
                r2[k] = keep + __shfl_xor_sync(~0u, send, 8);
            }
            const float keep = b2 ? r2[1] : r2[0], send = b2 ? r2[0] : r2[1];
            const float r1 = keep + __shfl_xor_sync(~0u, send, 4);
            red[(i & 1) * 256 + warp * 32 + j * 8 + g] = r1;
            cons_sync();
            if (warp == (i & 7)) {
                float y = 0.f;
#pragma unroll
                for (int w = 0; w < 8; w++) y += red[(i & 1) * 256 + w * 32 + lane];
                st_rlx1(&g_y1[t * 32 + lane], tagf(bf16r(y), tag));
            }
        }
    }
    TRACE(3);

    {
        uint32_t* q_s = reinterpret_cast<uint32_t*>(sptr + OFF_Q);
        uint4 w[4];
        int it = 0;
        bool all;
#pragma unroll
        for (int i = 0; i < 4; i++) w[i] = ld_rlx4(&g_y1[(i * 256 + tid) * 4]);
        do {
            all = true;
#pragma unroll
            for (int i = 0; i < 4; i++)
                if (!ok4(w[i], tag)) { w[i] = ld_rlx4(&g_y1[(i * 256 + tid) * 4]); all = false; }
        } while (!all && ++it < SPIN_LIMIT);
#pragma unroll
        for (int i = 0; i < 4; i++) {
            const int idx4 = i * 256 + tid, head = idx4 >> 5, dp = (idx4 & 31) * 2;
            const int ks = dp >> 3, r = dp & 7;
            const int pos = head * 64 + (r & 3) * 16 + ks * 2 + (r >> 2);
            q_s[pos] = (w[i].x >> 16) | (w[i].y & 0xffff0000u);
            q_s[pos + 16] = (w[i].z >> 16) | (w[i].w & 0xffff0000u);
        }
        cons_sync();
    }
    TRACE(4);

    {
        float* wmax = reinterpret_cast<float*>(sptr + OFF_WMAX);
        float* wsum = reinterpret_cast<float*>(sptr + OFF_WSUM);
        __nv_bfloat16* p_s = reinterpret_cast<__nv_bfloat16*>(sptr + OFF_P);
        const bool bl = (g == 0) || (g == 2);
        const int mi = lane >> 3, l7 = lane & 7;
        const uint32_t k_off = (16 * warp + l7 + (mi & 1) * 8) * 128;
        const uint32_t k_x = ((mi >> 1) ^ l7) << 4;
        const int vchunk = 2 * warp + (mi & 1);
        const uint32_t v_off = (vchunk >> 3) * 16384 + (l7 + (mi >> 1) * 8) * 128 + (((vchunk & 7) ^ l7) << 4);
        const uint32_t q_addr = sbase + OFF_Q + ((g >> 1) * 64 + j * 16) * 4;
        const uint32_t p_addr = sbase + OFF_P + (g >> 1) * 256 + j * 64;
        int nchunks = 0;
        while (true) {
            mbar_wait(bar_full + s * 8, ph);
            const int c = s_item[s];
            if (c < 0) break;
            nchunks++;
            uint32_t bf[16];
            if (bl) {
#pragma unroll
                for (int i = 0; i < 4; i++) {
                    const uint4 v = lds128(q_addr + (c >> 7) * 512 + i * 16);
                    bf[i * 4] = v.x; bf[i * 4 + 1] = v.y; bf[i * 4 + 2] = v.z; bf[i * 4 + 3] = v.w;
                }
            } else {
#pragma unroll
                for (int i = 0; i < 16; i++) bf[i] = 0u;
            }
            uint32_t a[8][4];
            {
                const uint32_t kb = sbase + s * STAGE_BYTES + k_off;
#pragma unroll
                for (int ks = 0; ks < 8; ks++) ldsm4(a[ks], kb + (ks >> 2) * 16384 + (k_x ^ ((ks & 3) << 5)));
            }
            float c0[4] = {0.f, 0.f, 0.f, 0.f}, c1[4] = {0.f, 0.f, 0.f, 0.f};
#pragma unroll
            for (int ks = 0; ks < 8; ks += 2) {
                mma16816(c0, a[ks], bf[2 * ks], bf[2 * ks + 1]);
                mma16816(c1, a[ks + 1], bf[2 * ks + 2], bf[2 * ks + 3]);
            }
            __syncwarp();
            if (lane == 0) mbar_arrive(bar_empty + s * 8);
            if (++s == NST) { s = 0; ph ^= 1; }
            const float sa = bf16r(bf16r(c0[0] + c1[0]) * 0.08838834764831845f);
            const float sb = bf16r(bf16r(c0[2] + c1[2]) * 0.08838834764831845f);
            float mx = fmaxf(sa, sb);
            mx = fmaxf(mx, __shfl_xor_sync(~0u, mx, 4));
            mx = fmaxf(mx, __shfl_xor_sync(~0u, mx, 8));
            mx = fmaxf(mx, __shfl_xor_sync(~0u, mx, 16));
            if (lane < 2) wmax[lane * 8 + warp] = mx;
            cons_sync();
            float m;
            {
                const float4 u = *reinterpret_cast<const float4*>(wmax + (j & 1) * 8);
                const float4 v = *reinterpret_cast<const float4*>(wmax + (j & 1) * 8 + 4);
                m = fmaxf(fmaxf(fmaxf(u.x, u.y), fmaxf(u.z, u.w)), fmaxf(fmaxf(v.x, v.y), fmaxf(v.z, v.w)));
            }
            const float ea = ex2((sa - m) * LOG2E), eb = ex2((sb - m) * LOG2E);
            if (j < 2) {
                const int pos = j * 128 + (g >> 1) * 32 + warp * 4 + (g & 1);
                p_s[pos] = __float2bfloat16_rn(ea);
                p_s[pos + 2] = __float2bfloat16_rn(eb);
            }
            float es = ea + eb;
            es += __shfl_xor_sync(~0u, es, 4);
            es += __shfl_xor_sync(~0u, es, 8);
            es += __shfl_xor_sync(~0u, es, 16);
            if (lane < 2) wsum[lane * 8 + warp] = es;
            mbar_wait(bar_full + s * 8, ph);
            {
                const uint32_t vb = sbase + s * STAGE_BYTES + v_off;
#pragma unroll
                for (int ks = 0; ks < 8; ks++) ldsm4t(a[ks], vb + ks * 2048);
            }
            cons_sync();
            if (bl) {
#pragma unroll
                for (int i = 0; i < 4; i++) {
                    const uint4 v = lds128(p_addr + i * 16);
                    bf[i * 4] = v.x; bf[i * 4 + 1] = v.y; bf[i * 4 + 2] = v.z; bf[i * 4 + 3] = v.w;
                }
            }
#pragma unroll
            for (int k = 0; k < 4; k++) { c0[k] = 0.f; c1[k] = 0.f; }
#pragma unroll
            for (int ks = 0; ks < 8; ks += 2) {
                mma16816(c0, a[ks], bf[2 * ks], bf[2 * ks + 1]);
                mma16816(c1, a[ks + 1], bf[2 * ks + 2], bf[2 * ks + 3]);
            }
            __syncwarp();
            if (lane == 0) mbar_arrive(bar_empty + s * 8);
            if (++s == NST) { s = 0; ph ^= 1; }
            if (j < 2) {
                float* rec = g_part + (size_t)(c * 2 + j) * REC + 16 * warp + g;
                st_rlx1(rec, tagf(c0[0] + c1[0], tag));
                st_rlx1(rec + 8, tagf(c0[2] + c1[2], tag));
            }
            if (warp == (c & 7)) {
                const int hh = (lane >> 3) & 1;
                const float mh = __shfl_sync(~0u, m, hh);
                const float4 u = *reinterpret_cast<const float4*>(wsum + hh * 8);
                const float4 v = *reinterpret_cast<const float4*>(wsum + hh * 8 + 4);
                const float l = ((u.x + u.y) + (u.z + u.w)) + ((v.x + v.y) + (v.z + v.w));
                if (lane < 16) st_rlx1(g_part + (size_t)(c * 2 + hh) * REC + 128 + l7, tagf((lane & 1) ? l : mh, tag));
            }
        }
        TRACEV(10, nchunks);
    }
    TRACE(5);

    {
        const int grp = tid / 72, cg = tid - grp * 72;
        float acc[8];
#pragma unroll
        for (int k = 0; k < 8; k++) acc[k] = 0.f;
        const float* h_s = reinterpret_cast<const float*>(sptr + OFF_H);
        mbar_wait(bar_h, 0);
        bool first = true;
        for (int r0 = wd0; r0 < wd1 || first; r0 += WD_PIECE) {
            if (!first) mbar_wait(bar_full + s * 8, ph);
            first = false;
            const int n = min(WD_PIECE, wd1 - r0);
            if (grp < 3) {
                const uint32_t a = sbase + s * STAGE_BYTES + cg * 16;
#pragma unroll 4
                for (int r = grp; r < n; r += 3) fma8(acc, h_s[r0 - wd0 + r], lds128(a + r * ROW_BYTES));
            }
            __syncwarp();
            if (lane == 0) mbar_arrive(bar_empty + s * 8);
            if (++s == NST) { s = 0; ph ^= 1; }
        }
        TRACE(6);
        float* cmb = reinterpret_cast<float*>(sptr + OFF_CMB);
        for (int t = b; t < 128; t += G) {
            const int hq = t >> 2;
            const float* rec0 = g_part + (size_t)((hq >> 1) * CH_PER_HEAD * 2 + (hq & 1)) * REC;
            const int c4 = tid & 7, ri = tid >> 3;
            uint4 o4[4]; uint2 ml[4];
            const float* po[4];
#pragma unroll
            for (int i = 0; i < 4; i++) {
                po[i] = rec0 + (size_t)(i * 32 + ri) * 2 * REC;
                o4[i] = ld_rlx4(po[i] + (t & 3) * 32 + c4 * 4);
                ml[i] = ld_rlx2(po[i] + 128 + (c4 & 3) * 2);
            }
            int it = 0;
            bool all;
            do {
                all = true;
#pragma unroll
                for (int i = 0; i < 4; i++) {
                    if (!ok4(o4[i], tag)) { o4[i] = ld_rlx4(po[i] + (t & 3) * 32 + c4 * 4); all = false; }
                    if (!ok2(ml[i], tag)) { ml[i] = ld_rlx2(po[i] + 128 + (c4 & 3) * 2); all = false; }
                }
            } while (!all && ++it < SPIN_LIMIT);
            float mw = fmaxf(fmaxf(untag(ml[0].x), untag(ml[1].x)), fmaxf(untag(ml[2].x), untag(ml[3].x)));
            mw = fmaxf(mw, __shfl_xor_sync(~0u, mw, 8));
            mw = fmaxf(mw, __shfl_xor_sync(~0u, mw, 16));
            float ox = 0.f, oy = 0.f, oz = 0.f, ow = 0.f, lw = 0.f;
#pragma unroll
            for (int i = 0; i < 4; i++) {
                const float f = ex2((untag(ml[i].x) - mw) * LOG2E);
                ox = fmaf(f, untag(o4[i].x), ox); oy = fmaf(f, untag(o4[i].y), oy);
                oz = fmaf(f, untag(o4[i].z), oz); ow = fmaf(f, untag(o4[i].w), ow);
                lw = fmaf(f, untag(ml[i].y), lw);
            }
#pragma unroll
            for (int o = 8; o <= 16; o <<= 1) {
                ox += __shfl_xor_sync(~0u, ox, o); oy += __shfl_xor_sync(~0u, oy, o);
                oz += __shfl_xor_sync(~0u, oz, o); ow += __shfl_xor_sync(~0u, ow, o);
                lw += __shfl_xor_sync(~0u, lw, o);
            }
            if (t != b) cons_sync();
            if (lane < 8) *reinterpret_cast<float4*>(cmb + warp * 36 + lane * 4) = make_float4(ox, oy, oz, ow);
            if (lane == 0) { cmb[warp * 36 + 32] = mw; cmb[warp * 36 + 33] = lw; }
            cons_sync();
            float M = cmb[32];
#pragma unroll
            for (int w = 1; w < 8; w++) M = fmaxf(M, cmb[w * 36 + 32]);
            float on = 0.f, L = 0.f;
#pragma unroll
            for (int w = 0; w < 8; w++) {
                const float f = ex2((cmb[w * 36 + 32] - M) * LOG2E);
                on = fmaf(f, cmb[w * 36 + lane], on);
                L = fmaf(f, cmb[w * 36 + 33], L);
            }
            const float ov = bf16r(on / L);
            TRACE(7);
            mbar_wait(bar_full + s * 8, ph);
            const uint32_t a = sbase + s * STAGE_BYTES + cg * 16;
#pragma unroll
            for (int i = 0; i < 11; i++) {
                const int r = grp + 3 * i;
                const float f = __shfl_sync(~0u, ov, r & 31);
                if (grp < 3 && r < 32) fma8(acc, f, lds128(a + r * ROW_BYTES));
            }
            __syncwarp();
            if (lane == 0) mbar_arrive(bar_empty + s * 8);
            if (++s == NST) { s = 0; ph ^= 1; }
        }
        float* red2 = reinterpret_cast<float*>(sptr + OFF_Q);
        if (grp < 3) {
            *reinterpret_cast<float4*>(red2 + grp * DM + cg * 8) = make_float4(acc[0], acc[1], acc[2], acc[3]);
            *reinterpret_cast<float4*>(red2 + grp * DM + cg * 8 + 4) = make_float4(acc[4], acc[5], acc[6], acc[7]);
        }
        cons_sync();
        if (tid < 144) {
            const float4 u = *reinterpret_cast<const float4*>(red2 + tid * 4);
            const float4 v = *reinterpret_cast<const float4*>(red2 + DM + tid * 4);
            const float4 w = *reinterpret_cast<const float4*>(red2 + 2 * DM + tid * 4);
            st_rlx4(&g_fin[b * DM + tid * 4],
                    make_uint4(tagf(u.x + v.x + w.x, tag), tagf(u.y + v.y + w.y, tag),
                               tagf(u.z + v.z + w.z, tag), tagf(u.w + v.w + w.w, tag)));
        }
    }
    TRACE(8);

    for (int k = b + warp * G; k < 144; k += 8 * G) {
        const float xv = lane < 4 ? __bfloat162float(prm.x[k * 4 + lane]) : 0.f;
        uint4 w[5];
        const uint4 idle = make_uint4(tag, tag, tag, tag);
#pragma unroll
        for (int i = 0; i < 5; i++) w[i] = (lane + 32 * i < G) ? ld_rlx4(&g_fin[(lane + 32 * i) * DM + k * 4]) : idle;
        int it = 0;
        bool all;
        do {
            all = true;
#pragma unroll
            for (int i = 0; i < 5; i++)
                if (!ok4(w[i], tag)) { w[i] = ld_rlx4(&g_fin[(lane + 32 * i) * DM + k * 4]); all = false; }
        } while (!all && ++it < SPIN_LIMIT);
        float sx = 0.f, sy = 0.f, sz = 0.f, sw = 0.f;
#pragma unroll
        for (int i = 0; i < 5; i++) { sx += untag(w[i].x); sy += untag(w[i].y); sz += untag(w[i].z); sw += untag(w[i].w); }
        __syncwarp();
        const bool b4 = lane & 16, b3 = lane & 8;
        const float r0 = (b4 ? sz : sx) + __shfl_xor_sync(~0u, b4 ? sx : sz, 16);
        const float r1 = (b4 ? sw : sy) + __shfl_xor_sync(~0u, b4 ? sy : sw, 16);
        float r = (b3 ? r1 : r0) + __shfl_xor_sync(~0u, b3 ? r0 : r1, 8);
        r += __shfl_xor_sync(~0u, r, 4);
        r += __shfl_xor_sync(~0u, r, 2);
        r += __shfl_xor_sync(~0u, r, 1);
        const float tot = __shfl_sync(~0u, r, (lane & 3) * 8);
        if (lane < 4) prm.out[k * 4 + lane] = __float2bfloat16_rn(xv + tot);
        if (k == 0 && lane == 0) st_rlx1(&g_epoch, epoch + 1u);
    }
    TRACE(9);
}

typedef CUresult (*EncodeFn)(CUtensorMap*, CUtensorMapDataType, cuuint32_t, void*, const cuuint64_t*, const cuuint64_t*,
                             const cuuint32_t*, const cuuint32_t*, CUtensorMapInterleave, CUtensorMapSwizzle,
                             CUtensorMapL2promotion, CUtensorMapFloatOOBfill);

void make_kv_map(EncodeFn enc, CUtensorMap* tm, const void* p) {
    cuuint64_t gd[3] = {64, (cuuint64_t)HKV * SK, 2};
    cuuint64_t gs[2] = {256, 128};
    cuuint32_t bx[3] = {64, CHUNK, 2};
    cuuint32_t es[3] = {1, 1, 1};
    enc(tm, CU_TENSOR_MAP_DATA_TYPE_BFLOAT16, 3, const_cast<void*>(p), gd, gs, bx, es, CU_TENSOR_MAP_INTERLEAVE_NONE,
        CU_TENSOR_MAP_SWIZZLE_128B, CU_TENSOR_MAP_L2_PROMOTION_L2_256B, CU_TENSOR_MAP_FLOAT_OOB_FILL_NONE);
}
void make_w1_map(EncodeFn enc, CUtensorMap* tm, const void* p, int cols) {
    cuuint64_t gd[3] = {(cuuint64_t)cols, 192, 3};
    cuuint64_t gs[2] = {(cuuint64_t)cols * 2, (cuuint64_t)cols * 2 * 192};
    cuuint32_t bx[3] = {32, 192, 3};
    cuuint32_t es[3] = {1, 1, 1};
    enc(tm, CU_TENSOR_MAP_DATA_TYPE_BFLOAT16, 3, const_cast<void*>(p), gd, gs, bx, es, CU_TENSOR_MAP_INTERLEAVE_NONE,
        CU_TENSOR_MAP_SWIZZLE_NONE, CU_TENSOR_MAP_L2_PROMOTION_L2_256B, CU_TENSOR_MAP_FLOAT_OOB_FILL_NONE);
}

}

extern "C" void kernel_launch(void* const* d_in, const int* in_sizes, int n_in, void* d_out, int out_size) {
    (void)in_sizes; (void)n_in; (void)out_size;
    void* fn = nullptr;
    cudaDriverEntryPointQueryResult qr;
    cudaGetDriverEntryPoint("cuTensorMapEncodeTiled", &fn, cudaEnableDefault, &qr);
    EncodeFn enc = (EncodeFn)fn;
    int dev = 0, sms = 0;
    cudaGetDevice(&dev);
    cudaDeviceGetAttribute(&sms, cudaDevAttrMultiProcessorCount, dev);
    const int G = sms < MAXG ? sms : MAXG;
    cudaFuncSetAttribute(fused_decode_kernel, cudaFuncAttributeMaxDynamicSharedMemorySize, SMEM_BYTES);

    CUtensorMap tk, tv, tq, tg, tu;
    make_kv_map(enc, &tk, d_in[1]);
    make_kv_map(enc, &tv, d_in[2]);
    make_w1_map(enc, &tq, d_in[3], QW);
    make_w1_map(enc, &tg, d_in[6], FF);
    make_w1_map(enc, &tu, d_in[7], FF);

    Params prm;
    prm.x = (const __nv_bfloat16*)d_in[0];
    prm.wo = (const __nv_bfloat16*)d_in[4];
    prm.wd = (const __nv_bfloat16*)d_in[8];
    prm.out = (__nv_bfloat16*)d_out;
    {
        int left = FF, total_left = FF + QW;
        prm.wd_start[0] = 0;
        for (int b = 0; b < G; b++) {
            int wo_rows = 0;
            for (int t = b; t < 128; t += G) wo_rows += 32;
            int target = (total_left + (G - b) - 1) / (G - b);
            int n = target - wo_rows;
            if (n < 0) n = 0;
            if (n > left || b == G - 1) n = left;
            prm.wd_start[b + 1] = (unsigned short)(prm.wd_start[b] + n);
            left -= n;
            total_left -= n + wo_rows;
        }
        for (int b = G; b < MAXG; b++) prm.wd_start[b + 1] = prm.wd_start[b];
    }
    fused_decode_kernel<<<G, NTHREADS, SMEM_BYTES>>>(tk, tv, tq, tg, tu, prm);
}
```

```cpp
#include <cuda_runtime.h>
#include <cuda.h>
#include <cuda_bf16.h>
#include <stdint.h>

namespace {

constexpr int DM = 576, HKV = 16, SK = 16384, FF = 4608, QW = 4096;
constexpr int CHUNK = 128;
constexpr int CH_PER_HEAD = SK / CHUNK;
constexpr int NCHUNK = HKV * CH_PER_HEAD;
constexpr int NUNIT = FF / 32;
constexpr int HALF = 18432;
constexpr int KV_HALF = 64 * 256;
constexpr int STAGE_BYTES = 2 * HALF;
#define NST 5
#define KH_ATT 4
#define KH_FILL 2
#define TAIL_CFG 1
#define CMB_MARGIN 160
#define INIT_HEADS 3
constexpr int REC = 136;
constexpr int MAXG = 144;
constexpr int NTHREADS = 416;
constexpr int SPIN_LIMIT = 1 << 20;

enum { ID_K = 0, ID_V = 1, ID_WQ = 2, ID_WG = 3, ID_WU = 4, ID_WD = 5, ID_WO = 6 };
constexpr int F_GATHER = 1 << 20;
constexpr int F_LAST = 1 << 21;
constexpr int MAXLIST = 24;

constexpr int OFF_Q = NST * STAGE_BYTES;
constexpr int OFF_P = OFF_Q + 8192;
constexpr int OFF_RED = OFF_P + 512;
constexpr int OFF_XN = OFF_RED + 1024;
constexpr int OFF_X = OFF_XN + 1152;
constexpr int OFF_WMAX = OFF_X + 1152;
constexpr int OFF_WSUM = OFF_WMAX + 64;
constexpr int OFF_CMB = OFF_WSUM + 64;
constexpr int OFF_COEF = OFF_CMB + 576;
constexpr int OFF_LIST = OFF_COEF + 640;
constexpr int OFF_ITEM = OFF_LIST + MAXLIST * 4;
constexpr int OFF_BAR = OFF_ITEM + 32;
constexpr int SMEM_BYTES = OFF_BAR + (3 * NST + 4) * 8;

struct Params {
    CUtensorMap tm[7];
    const __nv_bfloat16* x;
    __nv_bfloat16* out;
};

__device__ float g_part[NCHUNK * 2 * REC];
__device__ float g_q[QW];
__device__ float g_fin[MAXG * DM];
__device__ unsigned g_mark[MAXG];
__device__ unsigned g_epoch;
__device__ unsigned g_ctr;
#define TRACET(i, t)
#define TRACEV(i, v)
#define TRACE(i) TRACET(i, 0)

__device__ __forceinline__ uint32_t smem_u32(const void* p) { return (uint32_t)__cvta_generic_to_shared(p); }
__device__ __forceinline__ void mbar_init(uint32_t bar, int cnt) {
    asm volatile("mbarrier.init.shared::cta.b64 [%0], %1;" ::"r"(bar), "r"(cnt) : "memory");
}
__device__ __forceinline__ void mbar_expect_tx(uint32_t bar, uint32_t bytes) {
    asm volatile("mbarrier.arrive.expect_tx.shared::cta.b64 _, [%0], %1;" ::"r"(bar), "r"(bytes) : "memory");
}
__device__ __forceinline__ void mbar_arrive(uint32_t bar) {
    asm volatile("mbarrier.arrive.shared::cta.b64 _, [%0];" ::"r"(bar) : "memory");
}
__device__ __forceinline__ void mbar_wait(uint32_t bar, uint32_t parity) {
    uint32_t ok;
    int it = 0;
    do {
        asm volatile(
            "{\n.reg .pred p;\n"
            "mbarrier.try_wait.parity.shared::cta.b64 p, [%1], %2;\n"
            "selp.u32 %0, 1, 0, p;\n}"
            : "=r"(ok) : "r"(bar), "r"(parity) : "memory");
    } while (!ok && ++it < SPIN_LIMIT);
}
__device__ __forceinline__ void tma3d(uint32_t dst, const CUtensorMap* tm, int c0, int c1, int c2, uint32_t bar, uint64_t pol) {
    asm volatile(
        "cp.async.bulk.tensor.3d.shared::cluster.global.mbarrier::complete_tx::bytes.L2::cache_hint [%0], [%1, {%3,%4,%5}], [%2], %6;"
        ::"r"(dst), "l"(tm), "r"(bar), "r"(c0), "r"(c1), "r"(c2), "l"(pol) : "memory");
}
__device__ __forceinline__ void cons_sync() { asm volatile("bar.sync 1, 256;" ::: "memory"); }
__device__ __forceinline__ void help_sync() { asm volatile("bar.sync 2, 128;" ::: "memory"); }

__device__ __forceinline__ uint32_t lds32(uint32_t a) {
    uint32_t v;
    asm volatile("ld.shared.u32 %0, [%1];" : "=r"(v) : "r"(a));
    return v;
}
__device__ __forceinline__ uint4 lds128(uint32_t a) {
    uint4 v;
    asm volatile("ld.shared.v4.u32 {%0,%1,%2,%3}, [%4];" : "=r"(v.x), "=r"(v.y), "=r"(v.z), "=r"(v.w) : "r"(a));
    return v;
}
__device__ __forceinline__ void ldsm4(uint32_t* r, uint32_t a) {
    asm volatile("ldmatrix.sync.aligned.m8n8.x4.shared.b16 {%0,%1,%2,%3}, [%4];"
                 : "=r"(r[0]), "=r"(r[1]), "=r"(r[2]), "=r"(r[3]) : "r"(a));
}
__device__ __forceinline__ void ldsm4t(uint32_t* r, uint32_t a) {
    asm volatile("ldmatrix.sync.aligned.m8n8.x4.trans.shared.b16 {%0,%1,%2,%3}, [%4];"
                 : "=r"(r[0]), "=r"(r[1]), "=r"(r[2]), "=r"(r[3]) : "r"(a));
}
__device__ __forceinline__ void mma16816(float* c, const uint32_t* a, uint32_t b0, uint32_t b1) {
    asm volatile(
        "mma.sync.aligned.m16n8k16.row.col.f32.bf16.bf16.f32 {%0,%1,%2,%3}, {%4,%5,%6,%7}, {%8,%9}, {%0,%1,%2,%3};"
        : "+f"(c[0]), "+f"(c[1]), "+f"(c[2]), "+f"(c[3])
        : "r"(a[0]), "r"(a[1]), "r"(a[2]), "r"(a[3]), "r"(b0), "r"(b1));
}
__device__ __forceinline__ uint4 ld_rlx4(const void* p) {
    uint4 v;
    asm volatile("ld.relaxed.gpu.global.v4.u32 {%0,%1,%2,%3}, [%4];"
                 : "=r"(v.x), "=r"(v.y), "=r"(v.z), "=r"(v.w) : "l"(p) : "memory");
    return v;
}
__device__ __forceinline__ uint2 ld_rlx2(const void* p) {
    uint2 v;
    asm volatile("ld.relaxed.gpu.global.v2.u32 {%0,%1}, [%2];" : "=r"(v.x), "=r"(v.y) : "l"(p) : "memory");
    return v;
}
__device__ __forceinline__ uint32_t ld_rlx1(const void* p) {
    uint32_t v;
    asm volatile("ld.relaxed.gpu.global.u32 %0, [%1];" : "=r"(v) : "l"(p) : "memory");
    return v;
}
__device__ __forceinline__ void st_rlx1(void* p, uint32_t v) {
    asm volatile("st.relaxed.gpu.global.u32 [%0], %1;" ::"l"(p), "r"(v) : "memory");
}
__device__ __forceinline__ void st_rlx4(void* p, uint4 v) {
    asm volatile("st.relaxed.gpu.global.v4.u32 [%0], {%1,%2,%3,%4};" ::"l"(p), "r"(v.x), "r"(v.y), "r"(v.z), "r"(v.w) : "memory");
}
__device__ __forceinline__ uint32_t tagf(float v, uint32_t tag) { return (__float_as_uint(v) & ~1u) | tag; }
__device__ __forceinline__ float untag(uint32_t w) { return __uint_as_float(w & ~1u); }
__device__ __forceinline__ uint32_t mis2(uint32_t a, uint32_t b, uint32_t tag) {
    uint32_t r;
    asm("lop3.b32 %0, %1, %2, %3, 0x7e;" : "=r"(r) : "r"(a), "r"(b), "r"(tag));
    return r;
}
__device__ __forceinline__ bool ok4(uint4 v, uint32_t tag) { return ((mis2(v.x, v.y, tag) | mis2(v.z, v.w, tag)) & 1u) == 0u; }
__device__ __forceinline__ bool ok2(uint2 v, uint32_t tag) { return (mis2(v.x, v.y, tag) & 1u) == 0u; }
__device__ __forceinline__ float bf16r(float v) { return __bfloat162float(__float2bfloat16_rn(v)); }
__device__ __forceinline__ float blo(uint32_t w) { return __uint_as_float(w << 16); }
__device__ __forceinline__ float bhi(uint32_t w) { return __uint_as_float(w & 0xffff0000u); }
__device__ __forceinline__ float ex2(float v) { float r; asm("ex2.approx.ftz.f32 %0, %1;" : "=f"(r) : "f"(v)); return r; }
__device__ __forceinline__ float sum8(uint4 w) {
    return ((blo(w.x) + bhi(w.x)) + (blo(w.y) + bhi(w.y))) + ((blo(w.z) + bhi(w.z)) + (blo(w.w) + bhi(w.w)));
}
__device__ __forceinline__ float sq8(uint4 w, float m) {
    float a, s = 0.f;
    a = blo(w.x) - m; s = fmaf(a, a, s); a = bhi(w.x) - m; s = fmaf(a, a, s);
    a = blo(w.y) - m; s = fmaf(a, a, s); a = bhi(w.y) - m; s = fmaf(a, a, s);
    a = blo(w.z) - m; s = fmaf(a, a, s); a = bhi(w.z) - m; s = fmaf(a, a, s);
    a = blo(w.w) - m; s = fmaf(a, a, s); a = bhi(w.w) - m; s = fmaf(a, a, s);
    return s;
}
__device__ __forceinline__ uint32_t pack_bf16(float lo, float hi) {
    return (__float_as_uint(lo) >> 16) | (__float_as_uint(hi) & 0xffff0000u);
}

constexpr float LOG2E = 1.4426950408889634f;

__global__ void __launch_bounds__(NTHREADS, 1)
fused_decode_kernel(const __grid_constant__ Params prm) {
    extern __shared__ __align__(1024) uint8_t sptr[];
    const uint32_t sbase = smem_u32(sptr);
    const int tid = threadIdx.x, warp = tid >> 5, lane = tid & 31;
    const int b = blockIdx.x, G = gridDim.x;
    const uint32_t bar_full = sbase + OFF_BAR;
    const uint32_t bar_empty = bar_full + 2 * NST * 8;
    const uint32_t bar_go = bar_empty + NST * 8, bar_o = bar_go + 8, bar_tail = bar_o + 8, bar_mark = bar_tail + 8;
    volatile int* s_item = reinterpret_cast<volatile int*>(sptr + OFF_ITEM);
    TRACE(0);

    int fin_k = -1;
    uint32_t epoch;

    if (warp == 8) {
        uint64_t pol_s, pol_n;
        asm volatile("createpolicy.fractional.L2::evict_first.b64 %0, 1.0;" : "=l"(pol_s));
        asm volatile("createpolicy.fractional.L2::evict_normal.b64 %0, 1.0;" : "=l"(pol_n));
        const int u0 = 2 * G - 1 - b;
        const bool pre0 = b < 128 || u0 < NUNIT || TAIL_CFG < 2;
        int* list = reinterpret_cast<int*>(sptr + OFF_LIST);
        int npre = 0, nall = 0;
        if (lane == 0) {
            mbar_init(bar_full, 1);
            mbar_init(bar_full + 8, 1);
            if (pre0) {
                const CUtensorMap* tm = &prm.tm[b < 128 ? ID_WQ : ID_WG];
                const int t = b < 128 ? b : (u0 < NUNIT ? u0 : b);
                mbar_expect_tx(bar_full, HALF);
                tma3d(sbase, tm, t * 32, 0, 0, bar_full, pol_n);
                mbar_expect_tx(bar_full + 8, HALF);
                tma3d(sbase + HALF, tm, t * 32, 0, 3, bar_full + 8, pol_n);
            }
            TRACET(12, 256);
            for (int i = 2; i < 2 * NST; i++) mbar_init(bar_full + i * 8, 1);
            for (int i = 0; i < NST; i++) mbar_init(bar_empty + i * 8, 8);
            for (int i = 0; i < 4; i++) mbar_init(bar_go + i * 8, 1);
            int n = 0;
#pragma unroll 1
            for (int t = b; t < 128; t += G) list[n++] = ID_WQ << 16 | t;
#pragma unroll 1
            for (int u = u0; u < NUNIT; u += G) {
                list[n++] = ID_WG << 16 | u; list[n++] = ID_WU << 16 | u; list[n++] = ID_WD << 16 | u;
            }
            if (TAIL_CFG < 2) list[n++] = ID_WG << 16 | b;
            if (TAIL_CFG < 1) list[n++] = ID_WU << 16 | b;
            npre = n;
            if (npre) list[npre - 1] |= F_GATHER;
            if (TAIL_CFG >= 2) list[n++] = ID_WG << 16 | b;
            if (TAIL_CFG >= 1) list[n++] = ID_WU << 16 | b;
            list[n++] = ID_WD << 16 | b;
#pragma unroll 1
            for (int t = b; t < 128; t += G) list[n++] = ID_WO << 16 | t;
            list[n - 1] |= F_LAST;
            nall = n;
            s_item[0] = list[0];
            s_item[NST] = -1;
            asm volatile("fence.mbarrier_init.release.cluster;" ::: "memory");
        }
        __syncwarp();
        asm volatile("bar.arrive 3, %0;" ::"n"(NTHREADS) : "memory");
        if (lane == 0) {
            int s = pre0 ? 1 : 0; uint32_t ph = 1;
            int infl = pre0 ? 2 : 0;
            int lh = 0; uint32_t lph = 0;
            int li = pre0 ? 1 : 0;
            int c = b, nxt = 0;
            bool isv = false;
#pragma unroll 1
            while (li < nall) {
                int item, limit = KH_ATT;
                if (li == npre && c < NCHUNK) {
                    item = (isv ? ID_V << 16 : ID_K << 16) | c;
                } else {
                    item = list[li];
                    if (li >= npre) limit = KH_FILL;
                    li++;
                }
                const int id = (item >> 16) & 7, t = item & 0xffff;
                const bool col = id >= ID_WQ && id <= ID_WU;
                const int c0 = col ? t * 32 : 0;
                const int c1 = col ? 0 : (id <= ID_V ? t * CHUNK : t * 32);
                const int d1 = col ? 0 : (id <= ID_V ? 64 : 16);
                const uint32_t bytes = id <= ID_V ? KV_HALF : HALF;
                mbar_wait(bar_empty + s * 8, ph);
                s_item[s] = item;
#pragma unroll 1
                for (int h = 0; h < 2; h++) {
                    while (infl >= limit) {
                        mbar_wait(bar_full + lh * 8, lph);
                        if (++lh == 2 * NST) { lh = 0; lph ^= 1; }
                        infl--;
                    }
                    infl++;
                    const uint32_t fb = bar_full + (s * 2 + h) * 8;
                    mbar_expect_tx(fb, bytes);
                    tma3d(sbase + s * STAGE_BYTES + h * HALF, &prm.tm[id], c0, c1 + h * d1, col ? 3 * h : 0, fb,
                          col ? pol_n : pol_s);
                }
                if (++s == NST) { s = 0; ph ^= 1; }
                if (id == ID_K) {
                    nxt = G + (int)atomicInc(&g_ctr, NCHUNK - 1);
                    isv = true;
                } else if (id == ID_V) {
                    if (nxt >= NCHUNK) s_item[NST] = c;
                    c = nxt;
                    isv = false;
                }
            }
#define FIN_INFL 0
            while (infl > FIN_INFL) {
                mbar_wait(bar_full + lh * 8, lph);
                if (++lh == 2 * NST) { lh = 0; lph ^= 1; }
                infl--;
            }
            mbar_arrive(bar_tail);
        }
        __syncwarp();
        epoch = s_item[NST + 1];
        fin_k = b;
        TRACET(1, 256);
    } else {
        uint4 xa, xb, xc;
        uint32_t xmine = 0, xmine2 = 0;
        if (warp < 8) {
            const uint4* x4 = reinterpret_cast<const uint4*>(prm.x);
            xa = __ldg(x4 + lane); xb = __ldg(x4 + 32 + lane);
            xc = make_uint4(0, 0, 0, 0);
            if (lane < 8) xc = __ldg(x4 + 64 + lane);
            xmine = __ldg(reinterpret_cast<const uint32_t*>(prm.x) + tid);
            if (tid < 32) xmine2 = __ldg(reinterpret_cast<const uint32_t*>(prm.x) + 256 + tid);
        }
        epoch = ld_rlx1(&g_epoch);
        asm volatile("bar.sync 3, %0;" ::"n"(NTHREADS) : "memory");
        const uint32_t tag = (epoch + 1u) & 1u;
        if (tid == 0) s_item[NST + 1] = epoch;
        if (warp > 8) {
            const int hw = warp - 9;
            float* cmb = reinterpret_cast<float*>(sptr + OFF_CMB);
            __nv_bfloat16* o_s = reinterpret_cast<__nv_bfloat16*>(sptr + OFF_COEF + 512);
            {
                const uint32_t inv = tag ^ 1u;
                const uint4 iv = make_uint4(inv, inv, inv, inv);
                constexpr int n4 = INIT_HEADS * CH_PER_HEAD * 2 * REC / 4;
                float* base = g_part + (size_t)(HKV - INIT_HEADS) * CH_PER_HEAD * 2 * REC;
                for (int i = b * 128 + (tid - 288); i < n4; i += G * 128) st_rlx4(base + i * 4, iv);
                help_sync();
                if (hw == 3) {
                    if (lane == 0) { __threadfence(); st_rlx1(&g_mark[b], tag); }
                    __nanosleep(8000);
#pragma unroll 1
                    for (int i = lane; i < G; i += 32) {
                        int it = 0;
                        while (((ld_rlx1(&g_mark[i]) ^ tag) & 1u) && ++it < SPIN_LIMIT) __nanosleep(500);
                    }
                    __threadfence();
                    __syncwarp();
                    if (lane == 0) mbar_arrive(bar_mark);
                }
            }
            if (b < 128) mbar_wait(bar_go, 0);
            int ti = 0;
#pragma unroll 1
            for (int t = b; t < 128; t += G, ti++) {
                const int hq = t >> 2;
                const int c4 = lane & 7, ri = lane >> 3;
                const float* rec = g_part + (size_t)(((hq >> 1) * CH_PER_HEAD + hw * 32 + ri) * 2 + (hq & 1)) * REC;
                const float* po = rec + (t & 3) * 32 + c4 * 4;
                const float* pm = rec + 128 + (c4 & 3) * 2;
                uint4 o4[8]; uint2 ml[8];
#pragma unroll
                for (int i = 0; i < 8; i++) { o4[i].x = tag ^ 1u; ml[i].x = tag ^ 1u; o4[i].y = o4[i].z = o4[i].w = ml[i].y = tag; }
                int it = 0;
                bool all;
                do {
                    all = true;
#pragma unroll
                    for (int i = 0; i < 8; i++) {
                        if (!ok4(o4[i], tag)) { o4[i] = ld_rlx4(po + i * 8 * REC); all = false; }
                        if (!ok2(ml[i], tag)) { ml[i] = ld_rlx2(pm + i * 8 * REC); all = false; }
                    }
                } while (!all && ++it < SPIN_LIMIT);
                float mw = untag(ml[0].x);
#pragma unroll
                for (int i = 1; i < 8; i++) mw = fmaxf(mw, untag(ml[i].x));
                mw = fmaxf(mw, __shfl_xor_sync(~0u, mw, 8));
                mw = fmaxf(mw, __shfl_xor_sync(~0u, mw, 16));
                float ox = 0.f, oy = 0.f, oz = 0.f, ow = 0.f, lw = 0.f;
#pragma unroll
                for (int i = 0; i < 8; i++) {
                    const float f = ex2((untag(ml[i].x) - mw) * LOG2E);
                    ox = fmaf(f, untag(o4[i].x), ox); oy = fmaf(f, untag(o4[i].y), oy);
                    oz = fmaf(f, untag(o4[i].z), oz); ow = fmaf(f, untag(o4[i].w), ow);
                    lw = fmaf(f, untag(ml[i].y), lw);
                }
#pragma unroll
                for (int o = 8; o <= 16; o <<= 1) {
                    ox += __shfl_xor_sync(~0u, ox, o); oy += __shfl_xor_sync(~0u, oy, o);
                    oz += __shfl_xor_sync(~0u, oz, o); ow += __shfl_xor_sync(~0u, ow, o);
                    lw += __shfl_xor_sync(~0u, lw, o);
                }
                if (ti) help_sync();
                if (lane < 8) *reinterpret_cast<float4*>(cmb + hw * 36 + lane * 4) = make_float4(ox, oy, oz, ow);
                if (lane == 0) { cmb[hw * 36 + 32] = mw; cmb[hw * 36 + 33] = lw; }
                help_sync();
                if (hw == 0) {
                    const float M = fmaxf(fmaxf(cmb[32], cmb[36 + 32]), fmaxf(cmb[72 + 32], cmb[108 + 32]));
                    float on = 0.f, L = 0.f;
#pragma unroll
                    for (int w = 0; w < 4; w++) {
                        const float f = ex2((cmb[w * 36 + 32] - M) * LOG2E);
                        on = fmaf(f, cmb[w * 36 + lane], on);
                        L = fmaf(f, cmb[w * 36 + 33], L);
                    }
                    o_s[(ti & 1) * 32 + lane] = __float2bfloat16_rn(on / L);
                }
            }
            if (hw == 0) {
                __syncwarp();
                if (lane == 0) mbar_arrive(bar_o);
                TRACET(7, 288);
            } else if (b + hw * G < 144) {
                mbar_wait(bar_tail, 0);
                fin_k = b + hw * G;
            }
        } else {
            const int g = lane >> 2, j = lane & 3;
            const int mi = lane >> 3, l7 = lane & 7;
            float* const fin_dst = &g_fin[b * DM + warp * 72 + j * 8 + g];
            st_rlx1(fin_dst, tag ^ 1u);
            st_rlx1(fin_dst + 32, tag ^ 1u);
            if (j == 0) st_rlx1(fin_dst + 64, tag ^ 1u);
            {
                float s = sum8(xa) + sum8(xb) + sum8(xc);
#pragma unroll
                for (int o = 16; o; o >>= 1) s += __shfl_xor_sync(~0u, s, o);
                const float mean = s * (1.f / DM);
                float v = sq8(xa, mean) + sq8(xb, mean) + (lane < 8 ? sq8(xc, mean) : 0.f);
#pragma unroll
                for (int o = 16; o; o >>= 1) v += __shfl_xor_sync(~0u, v, o);
                const float mb = bf16r(mean);
                const float sd = bf16r(sqrtf(bf16r(bf16r(v * (1.f / DM)) + 1e-5f)));
                uint32_t* xn_s = reinterpret_cast<uint32_t*>(sptr + OFF_XN);
                xn_s[tid] = pack_bf16(bf16r(bf16r(blo(xmine) - mb) / sd), bf16r(bf16r(bhi(xmine) - mb) / sd));
                xn_s[288 + tid] = xmine;
                if (tid < 32) {
                    xn_s[256 + tid] = pack_bf16(bf16r(bf16r(blo(xmine2) - mb) / sd), bf16r(bf16r(bhi(xmine2) - mb) / sd));
                    xn_s[288 + 256 + tid] = xmine2;
                }
                cons_sync();
            }

            int s = 0; uint32_t ph = 0;
            int rb = 0;
            float acc[5][4];
#pragma unroll
            for (int i = 0; i < 5; i++) { acc[i][0] = 0.f; acc[i][1] = 0.f; acc[i][2] = 0.f; acc[i][3] = 0.f; }
            auto release = [&]() {
                __syncwarp();
                if (lane == 0) mbar_arrive(bar_empty + s * 8);
                if (++s == NST) { s = 0; ph ^= 1; }
            };
            float* wmax = reinterpret_cast<float*>(sptr + OFF_WMAX);
            float* wsum = reinterpret_cast<float*>(sptr + OFF_WSUM);
            __nv_bfloat16* p_s = reinterpret_cast<__nv_bfloat16*>(sptr + OFF_P);
            const bool bl = (g == 0) || (g == 2);
            const uint32_t k_off = (warp >> 2) * HALF + (16 * (warp & 3) + l7 + (mi & 1) * 8) * 128;
            const uint32_t k_x = ((mi >> 1) ^ l7) << 4;
            const int vchunk = 2 * warp + (mi & 1);
            const uint32_t v_off = (vchunk >> 3) * 8192 + (l7 + (mi >> 1) * 8) * 128 + (((vchunk & 7) ^ l7) << 4);
            const uint32_t q_addr = sbase + OFF_Q + ((g >> 1) * 64 + j * 16) * 4;
            const uint32_t p_addr = sbase + OFF_P + (g >> 1) * 256 + j * 64;
            int tl = b;
            while (tl + G < 128) tl += G;
            const int go_thr = ((tl >> 3) + 1) * CH_PER_HEAD + CMB_MARGIN;
            bool fired = false, have_q = false;
            int nwo = 0;
            float ygate = 0.f;
            int nchunks = 0;

#pragma unroll 1
            while (true) {
                mbar_wait(bar_full + (s * 2 + (warp >> 2)) * 8, ph);
                const int item = s_item[s];
                const int id = (item >> 16) & 7, c = item & 0xffff;
                if (id == ID_K && have_q) {
                    nchunks++;
                    if (c >= (HKV - INIT_HEADS) * CH_PER_HEAD) mbar_wait(bar_mark, 0);
                    uint32_t bf[16];
                    if (bl) {
#pragma unroll
                        for (int i = 0; i < 4; i++) {
                            const uint4 v = lds128(q_addr + (c >> 7) * 512 + i * 16);
                            bf[i * 4] = v.x; bf[i * 4 + 1] = v.y; bf[i * 4 + 2] = v.z; bf[i * 4 + 3] = v.w;
                        }
                    } else {
#pragma unroll
                        for (int i = 0; i < 16; i++) bf[i] = 0u;
                    }
                    uint32_t a[8][4];
                    {
                        const uint32_t kb = sbase + s * STAGE_BYTES + k_off;
#pragma unroll
                        for (int ks = 0; ks < 8; ks++) ldsm4(a[ks], kb + (ks >> 2) * 8192 + (k_x ^ ((ks & 3) << 5)));
                    }
                    float c0[4] = {0.f, 0.f, 0.f, 0.f}, c1[4] = {0.f, 0.f, 0.f, 0.f};
#pragma unroll
                    for (int ks = 0; ks < 8; ks += 2) {
                        mma16816(c0, a[ks], bf[2 * ks], bf[2 * ks + 1]);
                        mma16816(c1, a[ks + 1], bf[2 * ks + 2], bf[2 * ks + 3]);
                    }
                    release();
                    const float sa = bf16r(bf16r(c0[0] + c1[0]) * 0.08838834764831845f);
                    const float sb = bf16r(bf16r(c0[2] + c1[2]) * 0.08838834764831845f);
                    float mx = fmaxf(sa, sb);
                    mx = fmaxf(mx, __shfl_xor_sync(~0u, mx, 4));
                    mx = fmaxf(mx, __shfl_xor_sync(~0u, mx, 8));
                    mx = fmaxf(mx, __shfl_xor_sync(~0u, mx, 16));
                    if (lane < 2) wmax[lane * 8 + warp] = mx;
                    cons_sync();
                    float m;
                    {
                        const float4 u = *reinterpret_cast<const float4*>(wmax + (j & 1) * 8);
                        const float4 v = *reinterpret_cast<const float4*>(wmax + (j & 1) * 8 + 4);
                        m = fmaxf(fmaxf(fmaxf(u.x, u.y), fmaxf(u.z, u.w)), fmaxf(fmaxf(v.x, v.y), fmaxf(v.z, v.w)));
                    }
                    const float ea = ex2((sa - m) * LOG2E), eb = ex2((sb - m) * LOG2E);
                    if (j < 2) {
                        const int pos = j * 128 + (g >> 1) * 32 + warp * 4 + (g & 1);
                        p_s[pos] = __float2bfloat16_rn(ea);
                        p_s[pos + 2] = __float2bfloat16_rn(eb);
                    }
                    float es = ea + eb;
                    es += __shfl_xor_sync(~0u, es, 4);
                    es += __shfl_xor_sync(~0u, es, 8);
                    es += __shfl_xor_sync(~0u, es, 16);
                    if (lane < 2) wsum[lane * 8 + warp] = es;
                    cons_sync();
                    if (bl) {
#pragma unroll
                        for (int i = 0; i < 4; i++) {
                            const uint4 v = lds128(p_addr + i * 16);
                            bf[i * 4] = v.x; bf[i * 4 + 1] = v.y; bf[i * 4 + 2] = v.z; bf[i * 4 + 3] = v.w;
                        }
                    }
                    if (warp == (c & 7)) {
                        const int hh = (lane >> 3) & 1;
                        const float mh = __shfl_sync(~0u, m, hh);
                        const float4 u = *reinterpret_cast<const float4*>(wsum + hh * 8);
                        const float4 v = *reinterpret_cast<const float4*>(wsum + hh * 8 + 4);
                        const float l = ((u.x + u.y) + (u.z + u.w)) + ((v.x + v.y) + (v.z + v.w));
                        if (lane < 16) st_rlx1(g_part + (size_t)(c * 2 + hh) * REC + 128 + l7, tagf((lane & 1) ? l : mh, tag));
                    }
#pragma unroll
                    for (int k = 0; k < 4; k++) { c0[k] = 0.f; c1[k] = 0.f; }
#pragma unroll
                    for (int h = 0; h < 2; h++) {
                        mbar_wait(bar_full + (s * 2 + h) * 8, ph);
                        const uint32_t vb = sbase + s * STAGE_BYTES + h * HALF + v_off;
#pragma unroll
                        for (int ks = 0; ks < 4; ks++) ldsm4t(a[ks], vb + ks * 2048);
                        mma16816(c0, a[0], bf[8 * h], bf[8 * h + 1]);
                        mma16816(c1, a[1], bf[8 * h + 2], bf[8 * h + 3]);
                        mma16816(c0, a[2], bf[8 * h + 4], bf[8 * h + 5]);
                        mma16816(c1, a[3], bf[8 * h + 6], bf[8 * h + 7]);
                    }
                    if (j < 2) {
                        float* rec = g_part + (size_t)(c * 2 + j) * REC + 16 * warp + g;
                        st_rlx1(rec, tagf(c0[0] + c1[0], tag));
                        st_rlx1(rec + 8, tagf(c0[2] + c1[2], tag));
                    }
                    release();
                    if (tid == 0 && !fired && (c >= go_thr || c == s_item[NST])) { mbar_arrive(bar_go); fired = true; }
                    TRACE(5);
                    continue;
                }
                if (id >= ID_WD) {
                    if (id == ID_WO && tid == 0 && !fired) { mbar_arrive(bar_go); fired = true; }
                    uint32_t ca = sbase + OFF_COEF + warp * 64 + j * 4;
                    if (id == ID_WO) {
                        mbar_wait(bar_o, 0);
                        ca = sbase + OFF_COEF + 512 + (nwo & 1) * 64 + j * 4;
                        nwo++;
                    }
                    const uint32_t a0 = sbase + s * STAGE_BYTES + (l7 + (mi >> 1) * 8) * 128;
#pragma unroll 1
                    for (int h = 0; h < 2; h++) {
                        const uint32_t b0 = lds32(ca + h * 32), b1 = lds32(ca + h * 32 + 16);
                        mbar_wait(bar_full + (s * 2 + h) * 8, ph);
                        if (id == ID_WO) TRACE(11);
                        uint32_t a[5][4];
#pragma unroll
                        for (int i = 0; i < 5; i++) {
                            const int ch = warp * 9 + (i < 4 ? 2 * i + (mi & 1) : 8);
                            ldsm4t(a[i], a0 + h * HALF + (ch >> 3) * 2048 + (((ch & 7) ^ l7) << 4));
                        }
#pragma unroll
                        for (int i = 0; i < 5; i++) mma16816(acc[i], a[i], b0, b1);
                    }
                    if (item & F_LAST) break;
                    release();
                    if (id == ID_WD) TRACE(6);
                } else if (id != ID_K) {
                    const int kq = warp >> 1;
                    const uint32_t a0 = sbase + s * STAGE_BYTES + (kq * 144 + l7 + (mi >> 1) * 8) * 64 +
                                        ((((warp & 1) * 2 + (mi & 1)) ^ (l7 >> 1)) << 4);
                    const uint32_t xa_ = sbase + OFF_XN + (kq * 144 + 2 * j) * 2;
                    uint32_t a[9][4], xf[18];
#pragma unroll
                    for (int ks = 0; ks < 9; ks++) {
                        ldsm4t(a[ks], a0 + ks * 1024);
                        xf[2 * ks] = lds32(xa_ + ks * 32); xf[2 * ks + 1] = lds32(xa_ + ks * 32 + 16);
                    }
                    float c0[4] = {0.f, 0.f, 0.f, 0.f}, c1[4] = {0.f, 0.f, 0.f, 0.f};
#pragma unroll
                    for (int ks = 0; ks < 9; ks++) mma16816((ks & 1) ? c1 : c0, a[ks], xf[2 * ks], xf[2 * ks + 1]);
                    float* red = reinterpret_cast<float*>(sptr + OFF_RED) + rb * 128;
                    if (j < 2) red[kq * 32 + (warp & 1) * 16 + j * 8 + g] = j ? c0[2] + c1[2] : c0[0] + c1[0];
                    release();
                    rb ^= 1;
                    cons_sync();
                    const float y = bf16r((red[lane] + red[32 + lane]) + (red[64 + lane] + red[96 + lane]));
                    if (id == ID_WQ) {
                        if (warp == 0) st_rlx1(&g_q[c * 32 + lane], tagf(y, tag));
                        TRACE(2);
                    } else if (id == ID_WG) {
                        ygate = y;
                    } else {
                        const float sg = bf16r(ygate / (1.f + __expf(-ygate)));
                        reinterpret_cast<__nv_bfloat16*>(sptr + OFF_COEF)[warp * 32 + lane] = __float2bfloat16_rn(sg * y);
                        __syncwarp();
                    }
                }
                if ((item & F_GATHER) || id == ID_K) {
                    TRACE(3);
                    uint32_t* q_s = reinterpret_cast<uint32_t*>(sptr + OFF_Q);
                    uint4 w[4];
#pragma unroll
                    for (int i = 0; i < 4; i++) { w[i].x = tag ^ 1u; w[i].y = w[i].z = w[i].w = tag; }
                    int it = 0;
                    bool all;
                    do {
                        all = true;
#pragma unroll
                        for (int i = 0; i < 4; i++)
                            if (!ok4(w[i], tag)) { w[i] = ld_rlx4(&g_q[(i * 256 + tid) * 4]); all = false; }
                    } while (!all && ++it < SPIN_LIMIT);
#pragma unroll
                    for (int i = 0; i < 4; i++) {
                        const int idx4 = i * 256 + tid, head = idx4 >> 5, dp = (idx4 & 31) * 2;
                        const int ks = dp >> 3, r = dp & 7;
                        const int pos = head * 64 + (r & 3) * 16 + ks * 2 + (r >> 2);
                        q_s[pos] = (w[i].x >> 16) | (w[i].y & 0xffff0000u);
                        q_s[pos + 16] = (w[i].z >> 16) | (w[i].w & 0xffff0000u);
                    }
                    cons_sync();
                    have_q = true;
                    TRACE(4);
                }
            }
            const float v0 = (j & 2) ? ((j & 1) ? acc[1][2] : acc[1][0]) : ((j & 1) ? acc[0][2] : acc[0][0]);
            const float v1 = (j & 2) ? ((j & 1) ? acc[3][2] : acc[3][0]) : ((j & 1) ? acc[2][2] : acc[2][0]);
            st_rlx1(fin_dst, tagf(v0, tag));
            st_rlx1(fin_dst + 32, tagf(v1, tag));
            if (j == 0) st_rlx1(fin_dst + 64, tagf(acc[4][0], tag));
            TRACE(8);
            TRACEV(10, nchunks);
        }
    }

    const uint32_t tag = (epoch + 1u) & 1u;
#pragma unroll 1
    for (; fin_k >= 0 && fin_k < 144; fin_k += 4 * G) {
        const float* src = &g_fin[lane * DM + fin_k * 4];
        uint4 w[5];
#pragma unroll
        for (int i = 0; i < 5; i++) { w[i].x = (lane + 32 * i < G) ? tag ^ 1u : tag; w[i].y = w[i].z = w[i].w = tag; }
        int it = 0;
        bool all;
        float tot;
        do {
            bool ok[5];
            all = true;
#pragma unroll
            for (int i = 0; i < 5; i++) { ok[i] = ok4(w[i], tag); all = all && ok[i]; }
            float sx = 0.f, sy = 0.f, sz = 0.f, sw = 0.f;
#pragma unroll
            for (int i = 0; i < 5; i++) { sx += untag(w[i].x); sy += untag(w[i].y); sz += untag(w[i].z); sw += untag(w[i].w); }
#pragma unroll
            for (int i = 0; i < 5; i++)
                if (!ok[i]) w[i] = ld_rlx4(src + i * 32 * DM);
            all = __all_sync(~0u, all);
            const bool b4 = lane & 16, b3 = lane & 8;
            const float r0 = (b4 ? sz : sx) + __shfl_xor_sync(~0u, b4 ? sx : sz, 16);
            const float r1 = (b4 ? sw : sy) + __shfl_xor_sync(~0u, b4 ? sy : sw, 16);
            float r = (b3 ? r1 : r0) + __shfl_xor_sync(~0u, b3 ? r0 : r1, 8);
            r += __shfl_xor_sync(~0u, r, 4);
            r += __shfl_xor_sync(~0u, r, 2);
            r += __shfl_xor_sync(~0u, r, 1);
            tot = r;
        } while (!all && ++it < SPIN_LIMIT);
        if ((lane & 7) == 0) {
            const int col = fin_k * 4 + (lane >> 3);
            const float xv = __bfloat162float(reinterpret_cast<const __nv_bfloat16*>(sptr + OFF_X)[col]);
            prm.out[col] = __float2bfloat16_rn(xv + tot);
        }
        if (fin_k == 0 && lane == 0) st_rlx1(&g_epoch, epoch + 1u);
        TRACET(9, 256);
    }
}

typedef CUresult (*EncodeFn)(CUtensorMap*, CUtensorMapDataType, cuuint32_t, void*, const cuuint64_t*, const cuuint64_t*,
                             const cuuint32_t*, const cuuint32_t*, CUtensorMapInterleave, CUtensorMapSwizzle,
                             CUtensorMapL2promotion, CUtensorMapFloatOOBfill);

void make_map(EncodeFn enc, CUtensorMap* tm, const void* p, cuuint64_t d0, cuuint64_t d1, cuuint64_t d2,
              cuuint64_t s1, cuuint64_t s2, cuuint32_t b0, cuuint32_t b1, cuuint32_t b2, CUtensorMapSwizzle sw) {
    cuuint64_t gd[3] = {d0, d1, d2};
    cuuint64_t gs[2] = {s1, s2};
    cuuint32_t bx[3] = {b0, b1, b2};
    cuuint32_t es[3] = {1, 1, 1};
    enc(tm, CU_TENSOR_MAP_DATA_TYPE_BFLOAT16, 3, const_cast<void*>(p), gd, gs, bx, es, CU_TENSOR_MAP_INTERLEAVE_NONE,
        sw, CU_TENSOR_MAP_L2_PROMOTION_L2_256B, CU_TENSOR_MAP_FLOAT_OOB_FILL_NONE);
}

}

extern "C" void kernel_launch(void* const* d_in, const int* in_sizes, int n_in, void* d_out, int out_size) {
    (void)in_sizes; (void)n_in; (void)out_size;
    void* fn = nullptr;
    cudaDriverEntryPointQueryResult qr;
    cudaGetDriverEntryPoint("cuTensorMapEncodeTiled", &fn, cudaEnableDefault, &qr);
    EncodeFn enc = (EncodeFn)fn;
    int dev = 0, sms = 0;
    cudaGetDevice(&dev);
    cudaDeviceGetAttribute(&sms, cudaDevAttrMultiProcessorCount, dev);
    const int G = sms < MAXG ? sms : MAXG;
    cudaFuncSetAttribute(fused_decode_kernel, cudaFuncAttributeMaxDynamicSharedMemorySize, SMEM_BYTES);

    Params prm;
    make_map(enc, &prm.tm[ID_K], d_in[1], 64, (cuuint64_t)HKV * SK, 2, 256, 128, 64, 64, 2, CU_TENSOR_MAP_SWIZZLE_128B);
    make_map(enc, &prm.tm[ID_V], d_in[2], 64, (cuuint64_t)HKV * SK, 2, 256, 128, 64, 64, 2, CU_TENSOR_MAP_SWIZZLE_128B);
    make_map(enc, &prm.tm[ID_WQ], d_in[3], QW, 96, 6, QW * 2, QW * 2 * 96, 32, 96, 3, CU_TENSOR_MAP_SWIZZLE_64B);
    make_map(enc, &prm.tm[ID_WG], d_in[6], FF, 96, 6, FF * 2, FF * 2 * 96, 32, 96, 3, CU_TENSOR_MAP_SWIZZLE_64B);
    make_map(enc, &prm.tm[ID_WU], d_in[7], FF, 96, 6, FF * 2, FF * 2 * 96, 32, 96, 3, CU_TENSOR_MAP_SWIZZLE_64B);
    make_map(enc, &prm.tm[ID_WD], d_in[8], 64, FF, 9, DM * 2, 128, 64, 16, 9, CU_TENSOR_MAP_SWIZZLE_128B);
    make_map(enc, &prm.tm[ID_WO], d_in[4], 64, QW, 9, DM * 2, 128, 64, 16, 9, CU_TENSOR_MAP_SWIZZLE_128B);
    prm.x = (const __nv_bfloat16*)d_in[0];
    prm.out = (__nv_bfloat16*)d_out;
    fused_decode_kernel<<<G, NTHREADS, SMEM_BYTES>>>(prm);
}
```

```cpp
#include <cuda_runtime.h>
#include <cuda.h>
#include <cuda_bf16.h>
#include <stdint.h>

namespace {

constexpr int DM = 576, HKV = 16, SK = 16384, FF = 4608, QW = 4096;
constexpr int CHUNK = 128;
constexpr int CH_PER_HEAD = SK / CHUNK;
constexpr int NCHUNK = HKV * CH_PER_HEAD;
constexpr int NUNIT = FF / 32;
constexpr int HALF = 18432;
constexpr int KV_HALF = 64 * 256;
constexpr int STAGE_BYTES = 2 * HALF;
#define NST 5
#define KH_ATT 4
#define KH_FILL 2
#define KH_F0 KH_FILL
#define KH_F1 KH_FILL
#define KH_F2 KH_FILL
#define KH_END 6
#define END_CH 132
#define WU_PROMO CU_TENSOR_MAP_L2_PROMOTION_L2_256B
#define W2_PROMO CU_TENSOR_MAP_L2_PROMOTION_L2_256B
#define PRO_STAGES 2
#define TAIL_CFG 1
#define CMB_MARGIN 160
#define INIT_HEADS 3
constexpr int MAXG = 144;
constexpr int NTHREADS = 416;
constexpr int SPIN_LIMIT = 1 << 20;

enum { ID_K = 0, ID_V = 1, ID_WQ = 2, ID_WG = 3, ID_WU = 4, ID_WD = 5, ID_WO = 6 };
constexpr int F_GATHER = 1 << 20;
constexpr int F_LAST = 1 << 21;
constexpr int F_NEXT = 1 << 22;
constexpr int MAXLIST = 24;

constexpr int OFF_Q = NST * STAGE_BYTES;
constexpr int OFF_P = OFF_Q + 8192;
constexpr int OFF_RED = OFF_P + 512;
constexpr int OFF_XN = OFF_RED + 1024;
constexpr int OFF_X = OFF_XN + 1152;
constexpr int OFF_WMAX = OFF_X + 1152;
constexpr int OFF_WSUM = OFF_WMAX + 64;
constexpr int OFF_CMB = OFF_WSUM + 64;
constexpr int OFF_COEF = OFF_CMB + 576;
constexpr int OFF_LIST = OFF_COEF + 640;
constexpr int OFF_ITEM = OFF_LIST + MAXLIST * 4;
constexpr int OFF_BAR = OFF_ITEM + 32;
constexpr int SMEM_BYTES = OFF_BAR + (3 * NST + 4) * 8;

struct Params {
    CUtensorMap tm[7];
    const __nv_bfloat16* x;
    __nv_bfloat16* out;
};

__device__ __align__(128) float g_po[NCHUNK * 256];
__device__ __align__(128) float g_ml[NCHUNK * 8];
__device__ __align__(128) float g_q[QW];
__device__ __align__(128) float g_fin[MAXG * DM];
__device__ unsigned g_mark[MAXG];
__device__ unsigned g_epoch;
__device__ unsigned g_ctr;
#define TRACET(i, t)
#define TRACEV(i, v)
#define TRACE(i) TRACET(i, 0)

__device__ __forceinline__ uint32_t smem_u32(const void* p) { return (uint32_t)__cvta_generic_to_shared(p); }
__device__ __forceinline__ void mbar_init(uint32_t bar, int cnt) {
    asm volatile("mbarrier.init.shared::cta.b64 [%0], %1;" ::"r"(bar), "r"(cnt) : "memory");
}
__device__ __forceinline__ void mbar_expect_tx(uint32_t bar, uint32_t bytes) {
    asm volatile("mbarrier.arrive.expect_tx.shared::cta.b64 _, [%0], %1;" ::"r"(bar), "r"(bytes) : "memory");
}
__device__ __forceinline__ void mbar_arrive(uint32_t bar) {
    asm volatile("mbarrier.arrive.shared::cta.b64 _, [%0];" ::"r"(bar) : "memory");
}
__device__ __forceinline__ void mbar_wait(uint32_t bar, uint32_t parity) {
    uint32_t ok;
    int it = 0;
    do {
        asm volatile(
            "{\n.reg .pred p;\n"
            "mbarrier.try_wait.parity.shared::cta.b64 p, [%1], %2;\n"
            "selp.u32 %0, 1, 0, p;\n}"
            : "=r"(ok) : "r"(bar), "r"(parity) : "memory");
    } while (!ok && ++it < SPIN_LIMIT);
}
__device__ __forceinline__ void tma3d(uint32_t dst, const CUtensorMap* tm, int c0, int c1, int c2, uint32_t bar, uint64_t pol) {
    asm volatile(
        "cp.async.bulk.tensor.3d.shared::cluster.global.mbarrier::complete_tx::bytes.L2::cache_hint [%0], [%1, {%3,%4,%5}], [%2], %6;"
        ::"r"(dst), "l"(tm), "r"(bar), "r"(c0), "r"(c1), "r"(c2), "l"(pol) : "memory");
}
__device__ __forceinline__ void cons_sync() { asm volatile("bar.sync 1, 256;" ::: "memory"); }
__device__ __forceinline__ void help_sync() { asm volatile("bar.sync 2, 128;" ::: "memory"); }

__device__ __forceinline__ uint32_t lds32(uint32_t a) {
    uint32_t v;
    asm volatile("ld.shared.u32 %0, [%1];" : "=r"(v) : "r"(a));
    return v;
}
__device__ __forceinline__ uint4 lds128(uint32_t a) {
    uint4 v;
    asm volatile("ld.shared.v4.u32 {%0,%1,%2,%3}, [%4];" : "=r"(v.x), "=r"(v.y), "=r"(v.z), "=r"(v.w) : "r"(a));
    return v;
}
__device__ __forceinline__ void ldsm4(uint32_t* r, uint32_t a) {
    asm volatile("ldmatrix.sync.aligned.m8n8.x4.shared.b16 {%0,%1,%2,%3}, [%4];"
                 : "=r"(r[0]), "=r"(r[1]), "=r"(r[2]), "=r"(r[3]) : "r"(a));
}
__device__ __forceinline__ void ldsm4t(uint32_t* r, uint32_t a) {
    asm volatile("ldmatrix.sync.aligned.m8n8.x4.trans.shared.b16 {%0,%1,%2,%3}, [%4];"
                 : "=r"(r[0]), "=r"(r[1]), "=r"(r[2]), "=r"(r[3]) : "r"(a));
}
__device__ __forceinline__ void mma16816(float* c, const uint32_t* a, uint32_t b0, uint32_t b1) {
    asm volatile(
        "mma.sync.aligned.m16n8k16.row.col.f32.bf16.bf16.f32 {%0,%1,%2,%3}, {%4,%5,%6,%7}, {%8,%9}, {%0,%1,%2,%3};"
        : "+f"(c[0]), "+f"(c[1]), "+f"(c[2]), "+f"(c[3])
        : "r"(a[0]), "r"(a[1]), "r"(a[2]), "r"(a[3]), "r"(b0), "r"(b1));
}
__device__ __forceinline__ uint4 ld_rlx4(const void* p) {
    uint4 v;
    asm volatile("ld.relaxed.gpu.global.v4.u32 {%0,%1,%2,%3}, [%4];"
                 : "=r"(v.x), "=r"(v.y), "=r"(v.z), "=r"(v.w) : "l"(p) : "memory");
    return v;
}
__device__ __forceinline__ uint2 ld_rlx2(const void* p) {
    uint2 v;
    asm volatile("ld.relaxed.gpu.global.v2.u32 {%0,%1}, [%2];" : "=r"(v.x), "=r"(v.y) : "l"(p) : "memory");
    return v;
}
__device__ __forceinline__ uint32_t ld_rlx1(const void* p) {
    uint32_t v;
    asm volatile("ld.relaxed.gpu.global.u32 %0, [%1];" : "=r"(v) : "l"(p) : "memory");
    return v;
}
__device__ __forceinline__ void st_rlx1(void* p, uint32_t v) {
    asm volatile("st.relaxed.gpu.global.u32 [%0], %1;" ::"l"(p), "r"(v) : "memory");
}
__device__ __forceinline__ void st_rlx2(void* p, uint32_t a, uint32_t b) {
    asm volatile("st.relaxed.gpu.global.v2.u32 [%0], {%1,%2};" ::"l"(p), "r"(a), "r"(b) : "memory");
}
__device__ __forceinline__ void st_rlx4(void* p, uint4 v) {
    asm volatile("st.relaxed.gpu.global.v4.u32 [%0], {%1,%2,%3,%4};" ::"l"(p), "r"(v.x), "r"(v.y), "r"(v.z), "r"(v.w) : "memory");
}
__device__ __forceinline__ uint32_t tagf(float v, uint32_t tag) { return (__float_as_uint(v) & ~1u) | tag; }
__device__ __forceinline__ float untag(uint32_t w) { return __uint_as_float(w & ~1u); }
__device__ __forceinline__ uint32_t mis2(uint32_t a, uint32_t b, uint32_t tag) {
    uint32_t r;
    asm("lop3.b32 %0, %1, %2, %3, 0x7e;" : "=r"(r) : "r"(a), "r"(b), "r"(tag));
    return r;
}
__device__ __forceinline__ bool ok4(uint4 v, uint32_t tag) { return ((mis2(v.x, v.y, tag) | mis2(v.z, v.w, tag)) & 1u) == 0u; }
__device__ __forceinline__ bool ok2(uint2 v, uint32_t tag) { return (mis2(v.x, v.y, tag) & 1u) == 0u; }
__device__ __forceinline__ float bf16r(float v) { return __bfloat162float(__float2bfloat16_rn(v)); }
__device__ __forceinline__ float blo(uint32_t w) { return __uint_as_float(w << 16); }
__device__ __forceinline__ float bhi(uint32_t w) { return __uint_as_float(w & 0xffff0000u); }
__device__ __forceinline__ float ex2(float v) { float r; asm("ex2.approx.ftz.f32 %0, %1;" : "=f"(r) : "f"(v)); return r; }
__device__ __forceinline__ float sum8(uint4 w) {
    return ((blo(w.x) + bhi(w.x)) + (blo(w.y) + bhi(w.y))) + ((blo(w.z) + bhi(w.z)) + (blo(w.w) + bhi(w.w)));
}
__device__ __forceinline__ float sq8(uint4 w, float m) {
    float a, s = 0.f;
    a = blo(w.x) - m; s = fmaf(a, a, s); a = bhi(w.x) - m; s = fmaf(a, a, s);
    a = blo(w.y) - m; s = fmaf(a, a, s); a = bhi(w.y) - m; s = fmaf(a, a, s);
    a = blo(w.z) - m; s = fmaf(a, a, s); a = bhi(w.z) - m; s = fmaf(a, a, s);
    a = blo(w.w) - m; s = fmaf(a, a, s); a = bhi(w.w) - m; s = fmaf(a, a, s);
    return s;
}
__device__ __forceinline__ uint32_t pack_bf16(float lo, float hi) {
    return (__float_as_uint(lo) >> 16) | (__float_as_uint(hi) & 0xffff0000u);
}

constexpr float LOG2E = 1.4426950408889634f;

__global__ void __launch_bounds__(NTHREADS, 1)
fused_decode_kernel(const __grid_constant__ Params prm) {
    extern __shared__ __align__(1024) uint8_t sptr[];
    const uint32_t sbase = smem_u32(sptr);
    const int tid = threadIdx.x, warp = tid >> 5, lane = tid & 31;
    const int b = blockIdx.x, G = gridDim.x;
    const uint32_t bar_full = sbase + OFF_BAR;
    const uint32_t bar_empty = bar_full + 2 * NST * 8;
    const uint32_t bar_go = bar_empty + NST * 8, bar_o = bar_go + 8, bar_tail = bar_o + 8, bar_mark = bar_tail + 8;
    volatile int* s_item = reinterpret_cast<volatile int*>(sptr + OFF_ITEM);
    TRACE(0);

    if (warp == 8) {
        uint64_t pol_s, pol_n;
        asm volatile("createpolicy.fractional.L2::evict_first.b64 %0, 1.0;" : "=l"(pol_s));
        asm volatile("createpolicy.fractional.L2::evict_normal.b64 %0, 1.0;" : "=l"(pol_n));
        const int u0 = 2 * G - 1 - b;
        const int pro = (G >= 128 && TAIL_CFG < 2 && (b < 128 || u0 < NUNIT)) ? PRO_STAGES : 0;
        int* list = reinterpret_cast<int*>(sptr + OFF_LIST);
        int npre = 0, nall = 0;
        if (lane == 0) {
            const int uf = u0 < NUNIT ? u0 : b;
#pragma unroll
            for (int i = 0; i < 4; i++) mbar_init(bar_full + i * 8, 1);
            if (pro) {
#pragma unroll
                for (int i = 0; i < 2 * PRO_STAGES; i++) {
                    const CUtensorMap* tm = &prm.tm[(b < 128 ? ID_WQ : ID_WG) + (i >> 1)];
                    mbar_expect_tx(bar_full + i * 8, HALF);
                    tma3d(sbase + i * HALF, tm, ((i < 2 && b < 128) ? b : uf) * 32, 0, (i & 1) * 3, bar_full + i * 8, pol_n);
                }
            }
            TRACET(12, 256);
            for (int i = 4; i < 2 * NST; i++) mbar_init(bar_full + i * 8, 1);
            for (int i = 0; i < NST; i++) mbar_init(bar_empty + i * 8, 8);
            for (int i = 0; i < 4; i++) mbar_init(bar_go + i * 8, 1);
            int n = 0;
#pragma unroll 1
            for (int t = b; t < 128; t += G) list[n++] = ID_WQ << 16 | t;
#pragma unroll 1
            for (int u = u0; u < NUNIT; u += G) {
                list[n++] = ID_WG << 16 | u; list[n++] = ID_WU << 16 | u; list[n++] = ID_WD << 16 | u;
            }
            if (TAIL_CFG < 2) list[n++] = ID_WG << 16 | b;
            if (TAIL_CFG < 1) list[n++] = ID_WU << 16 | b;
            npre = n;
            if (npre) list[npre - 1] |= F_GATHER;
            if (TAIL_CFG >= 2) list[n++] = ID_WG << 16 | b;
            if (TAIL_CFG >= 1) list[n++] = ID_WU << 16 | b;
            list[n++] = ID_WD << 16 | b;
#pragma unroll 1
            for (int t = b; t < 128; t += G) list[n++] = ID_WO << 16 | t;
            list[n - 1] |= F_LAST;
#pragma unroll 1
            for (int i = npre; i + 1 < n; i++) list[i] |= F_NEXT | ((list[i + 1] >> 16) & 63) << 24;
            nall = n;
            s_item[0] = list[0];
            s_item[1] = list[1];
            s_item[NST] = -1;
            asm volatile("fence.mbarrier_init.release.cluster;" ::: "memory");
        }
        __syncwarp();
        asm volatile("bar.arrive 3, %0;" ::"n"(NTHREADS) : "memory");
        if (lane == 0) {
            int s = pro; uint32_t ph = 1;
            int infl = 2 * pro;
            int lh = 0; uint32_t lph = 0;
            int li = pro;
            int c = b, nxt = 0;
            bool isv = false;
#pragma unroll 1
            while (li < nall) {
                int item, limit = (c >= NCHUNK - END_CH) ? KH_END : KH_ATT;
                if (li == npre && c < NCHUNK) {
                    item = (isv ? ID_V << 16 : ID_K << 16) | c;
                } else {
                    item = list[li];
                    if (li >= npre) limit = li == npre ? KH_F0 : (li == npre + 1 ? KH_F1 : KH_F2);
                    li++;
                }
                const int id = (item >> 16) & 7, t = item & 0xffff;
                const bool col = id >= ID_WQ && id <= ID_WU;
                const int c0 = col ? t * 32 : 0;
                const int c1 = col ? 0 : (id <= ID_V ? t * CHUNK : (id == ID_WD ? t * 32 : (t >> 3) * 256 + (t & 7) * 16));
                const int d1 = col ? 0 : (id <= ID_V ? 64 : (id == ID_WD ? 16 : 128));
                const uint32_t bytes = id <= ID_V ? KV_HALF : HALF;
                mbar_wait(bar_empty + s * 8, ph);
                s_item[s] = item;
#pragma unroll 1
                for (int h = 0; h < 2; h++) {
                    while (infl >= limit) {
                        mbar_wait(bar_full + lh * 8, lph);
                        if (++lh == 2 * NST) { lh = 0; lph ^= 1; }
                        infl--;
                    }
                    infl++;
                    const uint32_t fb = bar_full + (s * 2 + h) * 8;
                    mbar_expect_tx(fb, bytes);
                    tma3d(sbase + s * STAGE_BYTES + h * HALF, &prm.tm[id], c0, c1 + h * d1, col ? 3 * h : 0, fb,
                          col ? pol_n : pol_s);
                }
                if (++s == NST) { s = 0; ph ^= 1; }
                if (id == ID_K) {
                    nxt = G + (int)atomicInc(&g_ctr, NCHUNK - 1);
                    isv = true;
                } else if (id == ID_V) {
                    if (nxt >= NCHUNK) s_item[NST] = c;
                    c = nxt;
                    isv = false;
                }
            }
#define FIN_INFL 0
            while (infl > FIN_INFL) {
                mbar_wait(bar_full + lh * 8, lph);
                if (++lh == 2 * NST) { lh = 0; lph ^= 1; }
                infl--;
            }
            mbar_arrive(bar_tail);
        }
        TRACET(1, 256);
    } else {
        uint4 xa, xb, xc;
        uint32_t xmine = 0, xmine2 = 0;
        if (warp < 8) {
            const uint4* x4 = reinterpret_cast<const uint4*>(prm.x);
            xa = __ldg(x4 + lane); xb = __ldg(x4 + 32 + lane);
            xc = make_uint4(0, 0, 0, 0);
            if (lane < 8) xc = __ldg(x4 + 64 + lane);
            xmine = __ldg(reinterpret_cast<const uint32_t*>(prm.x) + tid);
            if (tid < 32) xmine2 = __ldg(reinterpret_cast<const uint32_t*>(prm.x) + 256 + tid);
        }
        const uint32_t epoch = ld_rlx1(&g_epoch);
        asm volatile("bar.sync 3, %0;" ::"n"(NTHREADS) : "memory");
        const uint32_t tag = (epoch + 1u) & 1u;
        if (warp > 8) {
            const int hw = warp - 9;
            float* cmb = reinterpret_cast<float*>(sptr + OFF_CMB);
            __nv_bfloat16* o_s = reinterpret_cast<__nv_bfloat16*>(sptr + OFF_COEF + 512);
            {
                const uint32_t inv = tag ^ 1u;
                const uint4 iv = make_uint4(inv, inv, inv, inv);
                constexpr int c_lo = (HKV - INIT_HEADS) * CH_PER_HEAD, n_o = INIT_HEADS * CH_PER_HEAD * 64;
#pragma unroll 1
                for (int i = b * 128 + (tid - 288); i < n_o + n_o / 32; i += G * 128)
                    st_rlx4(i < n_o ? g_po + c_lo * 256 + i * 4 : g_ml + c_lo * 8 + (i - n_o) * 4, iv);
            }
#pragma unroll 1
            for (int pass = 0; pass < 2; pass++) {
                const uint32_t miss = tag ^ pass;
                if (pass && b < 128) mbar_wait(bar_go, 0);
                int ti = 0;
#pragma unroll 1
                for (int t = pass ? b : 127; t < 128; t += G, ti++) {
                    const int c4 = lane & 7, ri = lane >> 3;
                    const int cr = (t >> 3) * CH_PER_HEAD + hw * 32 + ri;
                    const float* po = g_po + (size_t)cr * 256 + (t & 7) * 32 + c4 * 4;
                    const float* pm = g_ml + cr * 8 + (c4 >> 2) * 2;
                    uint4 o4[8]; uint2 ml[8];
#pragma unroll
                    for (int i = 0; i < 8; i++) { o4[i] = make_uint4(miss, tag, tag, tag); ml[i] = make_uint2(miss, tag); }
                    int it = 0;
                    bool all;
                    do {
                        all = true;
#pragma unroll
                        for (int i = 0; i < 8; i++) {
                            if (!ok4(o4[i], tag)) { o4[i] = ld_rlx4(po + i * 1024); all = false; }
                            if (!ok2(ml[i], tag)) { ml[i] = ld_rlx2(pm + i * 32); all = false; }
                        }
                    } while (!all && ++it < SPIN_LIMIT);
                    float mw = untag(ml[0].x);
#pragma unroll
                    for (int i = 1; i < 8; i++) mw = fmaxf(mw, untag(ml[i].x));
                    mw = fmaxf(mw, __shfl_xor_sync(~0u, mw, 8));
                    mw = fmaxf(mw, __shfl_xor_sync(~0u, mw, 16));
                    float ox = 0.f, oy = 0.f, oz = 0.f, ow = 0.f, lw = 0.f;
#pragma unroll
                    for (int i = 0; i < 8; i++) {
                        const float f = ex2((untag(ml[i].x) - mw) * LOG2E);
                        ox = fmaf(f, untag(o4[i].x), ox); oy = fmaf(f, untag(o4[i].y), oy);
                        oz = fmaf(f, untag(o4[i].z), oz); ow = fmaf(f, untag(o4[i].w), ow);
                        lw = fmaf(f, untag(ml[i].y), lw);
                    }
#pragma unroll
                    for (int o = 8; o <= 16; o <<= 1) {
                        ox += __shfl_xor_sync(~0u, ox, o); oy += __shfl_xor_sync(~0u, oy, o);
                        oz += __shfl_xor_sync(~0u, oz, o); ow += __shfl_xor_sync(~0u, ow, o);
                        lw += __shfl_xor_sync(~0u, lw, o);
                    }
                    if (ti) help_sync();
                    if (lane < 8) *reinterpret_cast<float4*>(cmb + hw * 36 + lane * 4) = make_float4(ox, oy, oz, ow);
                    if (lane == 0 || lane == 4) { cmb[hw * 36 + 32 + (lane >> 1)] = mw; cmb[hw * 36 + 33 + (lane >> 1)] = lw; }
                    help_sync();
                    if (hw == 0) {
                        const float* mlp = cmb + 32 + (lane >> 4) * 2;
                        const float M = fmaxf(fmaxf(mlp[0], mlp[36]), fmaxf(mlp[72], mlp[108]));
                        float on = 0.f, L = 0.f;
#pragma unroll
                        for (int w = 0; w < 4; w++) {
                            const float f = ex2((mlp[w * 36] - M) * LOG2E);
                            on = fmaf(f, cmb[w * 36 + lane], on);
                            L = fmaf(f, mlp[w * 36 + 1], L);
                        }
                        o_s[(ti & 1) * 32 + (lane & 16) + ((lane & 15) >> 1) + (lane & 1) * 8] = __float2bfloat16_rn(on / L);
                    }
                }
                if (hw == 0) {
                    __syncwarp();
                    if (lane == 0 && pass) mbar_arrive(bar_o);
                    TRACET(7, 288);
                } else if (hw == 3) {
                    if (pass == 0) {
                        if (lane == 0) { __threadfence(); st_rlx1(&g_mark[b], tag); }
                        __nanosleep(8000);
#pragma unroll 1
                        for (int i = lane; i < G; i += 32) {
                            int it = 0;
                            while (((ld_rlx1(&g_mark[i]) ^ tag) & 1u) && ++it < SPIN_LIMIT) __nanosleep(500);
                        }
                        __threadfence();
                        __syncwarp();
                        if (lane == 0) mbar_arrive(bar_mark);
                    }
                } else {
                    int k = pass ? b + (hw - 1) * G : 143;
                    if (pass && k < 144) mbar_wait(bar_tail, 0);
#pragma unroll 1
                    for (; k < 144; k += 2 * G) {
                        const float* src = &g_fin[lane * DM + k * 4];
                        uint4 w[5];
#pragma unroll
                        for (int i = 0; i < 5; i++) w[i] = make_uint4(lane + 32 * i < G ? miss : tag, tag, tag, tag);
                        int it = 0;
                        bool all;
                        do {
                            all = true;
#pragma unroll
                            for (int i = 0; i < 5; i++)
                                if (!ok4(w[i], tag)) { w[i] = ld_rlx4(src + i * 32 * DM); all = false; }
                            all = __all_sync(~0u, all);
                        } while (!all && ++it < SPIN_LIMIT);
                        float sx = 0.f, sy = 0.f, sz = 0.f, sw = 0.f;
#pragma unroll
                        for (int i = 0; i < 5; i++) { sx += untag(w[i].x); sy += untag(w[i].y); sz += untag(w[i].z); sw += untag(w[i].w); }
                        const bool b4 = lane & 16, b3 = lane & 8;
                        const float r0 = (b4 ? sz : sx) + __shfl_xor_sync(~0u, b4 ? sx : sz, 16);
                        const float r1 = (b4 ? sw : sy) + __shfl_xor_sync(~0u, b4 ? sy : sw, 16);
                        float r = (b3 ? r1 : r0) + __shfl_xor_sync(~0u, b3 ? r0 : r1, 8);
                        r += __shfl_xor_sync(~0u, r, 4);
                        r += __shfl_xor_sync(~0u, r, 2);
                        r += __shfl_xor_sync(~0u, r, 1);
                        const int col = k * 4 + (lane >> 3);
                        const float xv = __bfloat162float(reinterpret_cast<const __nv_bfloat16*>(sptr + OFF_X)[col]);
                        if ((lane & 7) == 0 && pass) prm.out[col] = __float2bfloat16_rn(xv + r);
                        if (k == 0 && lane == 0) st_rlx1(&g_epoch, epoch + 1u);
                        TRACET(9, 320);
                    }
                }
                if (pass == 0) help_sync();
            }
        } else {
            const int g = lane >> 2, j = lane & 3;
            const int mi = lane >> 3, l7 = lane & 7;
            float* const fin_dst = &g_fin[b * DM + warp * 72 + j * 8 + g];
            {
                float s = sum8(xa) + sum8(xb) + sum8(xc);
#pragma unroll
                for (int o = 16; o; o >>= 1) s += __shfl_xor_sync(~0u, s, o);
                const float mean = s * (1.f / DM);
                float v = sq8(xa, mean) + sq8(xb, mean) + (lane < 8 ? sq8(xc, mean) : 0.f);
#pragma unroll
                for (int o = 16; o; o >>= 1) v += __shfl_xor_sync(~0u, v, o);
                const float mb = bf16r(mean);
                const float sd = bf16r(sqrtf(bf16r(bf16r(v * (1.f / DM)) + 1e-5f)));
                uint32_t* xn_s = reinterpret_cast<uint32_t*>(sptr + OFF_XN);
                xn_s[tid] = pack_bf16(bf16r(bf16r(blo(xmine) - mb) / sd), bf16r(bf16r(bhi(xmine) - mb) / sd));
                xn_s[288 + tid] = xmine;
                if (tid < 32) {
                    xn_s[256 + tid] = pack_bf16(bf16r(bf16r(blo(xmine2) - mb) / sd), bf16r(bf16r(bhi(xmine2) - mb) / sd));
                    xn_s[288 + 256 + tid] = xmine2;
                }
                cons_sync();
            }

            int s = 0; uint32_t ph = 0;
            int rb = 0;
            float acc[5][4];
#pragma unroll
            for (int i = 0; i < 5; i++) { acc[i][0] = 0.f; acc[i][1] = 0.f; acc[i][2] = 0.f; acc[i][3] = 0.f; }
            auto release = [&]() {
                __syncwarp();
                if (lane == 0) mbar_arrive(bar_empty + s * 8);
                if (++s == NST) { s = 0; ph ^= 1; }
            };
            float* wmax = reinterpret_cast<float*>(sptr + OFF_WMAX);
            float* wsum = reinterpret_cast<float*>(sptr + OFF_WSUM);
            __nv_bfloat16* p_s = reinterpret_cast<__nv_bfloat16*>(sptr + OFF_P);
            const bool bl = (g == 0) || (g == 2);
            const uint32_t k_off = (warp >> 2) * HALF + (16 * (warp & 3) + l7 + (mi & 1) * 8) * 128;
            const uint32_t k_x = ((mi >> 1) ^ l7) << 4;
            const int vchunk = 2 * warp + (mi & 1);
            const uint32_t v_off = (vchunk >> 3) * 8192 + (l7 + (mi >> 1) * 8) * 128 + (((vchunk & 7) ^ l7) << 4);
            const uint32_t q_addr = sbase + OFF_Q + ((g >> 1) * 64 + j * 16) * 4;
            const uint32_t p_addr = sbase + OFF_P + (g >> 1) * 256 + j * 64;
            int tl = b;
            while (tl + G < 128) tl += G;
            const int go_thr = ((tl >> 3) + 1) * CH_PER_HEAD + CMB_MARGIN;
            bool fired = false, have_q = false;
            int nwo = 0;
            float ygate = 0.f;
            int nchunks = 0;

            bool dry = true;
            int known = ID_WD << 16 | F_LAST;
#pragma unroll 1
            while (true) {
                const bool early = ((known >> 16) & 7) >= ID_WD;
                if (!early) mbar_wait(bar_full + (s * 2 + (warp >> 2)) * 8, ph);
                int item = early ? known : s_item[s];
                known = 0;
                const int id = (item >> 16) & 7, c = item & 0xffff;
                if (id == ID_K && have_q) {
                    nchunks++;
                    if (c >= (HKV - INIT_HEADS) * CH_PER_HEAD) mbar_wait(bar_mark, 0);
                    uint32_t bf[16];
                    if (bl) {
#pragma unroll
                        for (int i = 0; i < 4; i++) {
                            const uint4 v = lds128(q_addr + (c >> 7) * 512 + i * 16);
                            bf[i * 4] = v.x; bf[i * 4 + 1] = v.y; bf[i * 4 + 2] = v.z; bf[i * 4 + 3] = v.w;
                        }
                    } else {
#pragma unroll
                        for (int i = 0; i < 16; i++) bf[i] = 0u;
                    }
                    uint32_t a[8][4];
                    {
                        const uint32_t kb = sbase + s * STAGE_BYTES + k_off;
#pragma unroll
                        for (int ks = 0; ks < 8; ks++) ldsm4(a[ks], kb + (ks >> 2) * 8192 + (k_x ^ ((ks & 3) << 5)));
                    }
                    float c0[4] = {0.f, 0.f, 0.f, 0.f}, c1[4] = {0.f, 0.f, 0.f, 0.f};
#pragma unroll
                    for (int ks = 0; ks < 8; ks += 2) {
                        mma16816(c0, a[ks], bf[2 * ks], bf[2 * ks + 1]);
                        mma16816(c1, a[ks + 1], bf[2 * ks + 2], bf[2 * ks + 3]);
                    }
                    release();
                    const float sa = bf16r(bf16r(c0[0] + c1[0]) * 0.08838834764831845f);
                    const float sb = bf16r(bf16r(c0[2] + c1[2]) * 0.08838834764831845f);
                    float mx = fmaxf(sa, sb);
                    mx = fmaxf(mx, __shfl_xor_sync(~0u, mx, 4));
                    mx = fmaxf(mx, __shfl_xor_sync(~0u, mx, 8));
                    mx = fmaxf(mx, __shfl_xor_sync(~0u, mx, 16));
                    if (lane < 2) wmax[lane * 8 + warp] = mx;
                    cons_sync();
                    float m;
                    {
                        const float4 u = *reinterpret_cast<const float4*>(wmax + (j & 1) * 8);
                        const float4 v = *reinterpret_cast<const float4*>(wmax + (j & 1) * 8 + 4);
                        m = fmaxf(fmaxf(fmaxf(u.x, u.y), fmaxf(u.z, u.w)), fmaxf(fmaxf(v.x, v.y), fmaxf(v.z, v.w)));
                    }
                    const float ea = ex2((sa - m) * LOG2E), eb = ex2((sb - m) * LOG2E);
                    if (j < 2) {
                        const int pos = j * 128 + (g >> 1) * 32 + warp * 4 + (g & 1);
                        p_s[pos] = __float2bfloat16_rn(ea);
                        p_s[pos + 2] = __float2bfloat16_rn(eb);
                    }
                    float es = ea + eb;
                    es += __shfl_xor_sync(~0u, es, 4);
                    es += __shfl_xor_sync(~0u, es, 8);
                    es += __shfl_xor_sync(~0u, es, 16);
                    if (lane < 2) wsum[lane * 8 + warp] = es;
                    cons_sync();
                    if (bl) {
#pragma unroll
                        for (int i = 0; i < 4; i++) {
                            const uint4 v = lds128(p_addr + i * 16);
                            bf[i * 4] = v.x; bf[i * 4 + 1] = v.y; bf[i * 4 + 2] = v.z; bf[i * 4 + 3] = v.w;
                        }
                    }
                    if (warp == (c & 7)) {
                        const int hh = (lane >> 1) & 1;
                        const float mh = __shfl_sync(~0u, m, hh);
                        const float4 u = *reinterpret_cast<const float4*>(wsum + hh * 8);
                        const float4 v = *reinterpret_cast<const float4*>(wsum + hh * 8 + 4);
                        const float l = ((u.x + u.y) + (u.z + u.w)) + ((v.x + v.y) + (v.z + v.w));
                        if (lane < 8) st_rlx1(g_ml + c * 8 + lane, tagf((lane & 1) ? l : mh, tag));
                    }
#pragma unroll
                    for (int k = 0; k < 4; k++) { c0[k] = 0.f; c1[k] = 0.f; }
#pragma unroll
                    for (int h = 0; h < 2; h++) {
                        mbar_wait(bar_full + (s * 2 + h) * 8, ph);
                        const uint32_t vb = sbase + s * STAGE_BYTES + h * HALF + v_off;
#pragma unroll
                        for (int ks = 0; ks < 4; ks++) ldsm4t(a[ks], vb + ks * 2048);
                        mma16816(c0, a[0], bf[8 * h], bf[8 * h + 1]);
                        mma16816(c1, a[1], bf[8 * h + 2], bf[8 * h + 3]);
                        mma16816(c0, a[2], bf[8 * h + 4], bf[8 * h + 5]);
                        mma16816(c1, a[3], bf[8 * h + 6], bf[8 * h + 7]);
                    }
                    if (j < 2)
                        st_rlx2(g_po + (size_t)c * 256 + warp * 32 + j * 16 + g * 2,
                                tagf(c0[0] + c1[0], tag), tagf(c0[2] + c1[2], tag));
                    release();
                    if (tid == 0 && !fired && (c >= go_thr || c == s_item[NST])) { mbar_arrive(bar_go); fired = true; }
                    TRACE(5);
                    continue;
                }
                if (id >= ID_WD) {
                    if (id == ID_WO && tid == 0 && !fired) { mbar_arrive(bar_go); fired = true; }
                    uint32_t ca = sbase + OFF_COEF + warp * 64 + j * 4;
                    if (id == ID_WO) {
                        mbar_wait(bar_o, 0);
                        ca = sbase + OFF_COEF + 512 + (nwo & 1) * 64 + j * 4;
                        nwo++;
                    }
                    const uint32_t a0 = sbase + s * STAGE_BYTES + (l7 + (mi >> 1) * 8) * 128;
#pragma unroll 1
                    for (int h = 0; h < 2; h++) {
                        const uint32_t b0 = lds32(ca + h * 32), b1 = lds32(ca + h * 32 + 16);
                        if (!dry) mbar_wait(bar_full + (s * 2 + h) * 8, ph);
                        if (id == ID_WO && h) TRACE(11);
                        uint32_t a[5][4];
#pragma unroll
                        for (int i = 0; i < 5; i++) {
                            const int ch = warp * 9 + (i < 4 ? 2 * i + (mi & 1) : 8);
                            ldsm4t(a[i], a0 + h * HALF + (ch >> 3) * 2048 + (((ch & 7) ^ l7) << 4));
                        }
#pragma unroll
                        for (int i = 0; i < 5; i++) mma16816(acc[i], a[i], b0, b1);
                    }
                    if (item & F_LAST) {
                        const uint32_t tg = dry ? tag ^ 1u : tag;
                        const float v0 = (j & 2) ? ((j & 1) ? acc[1][2] : acc[1][0]) : ((j & 1) ? acc[0][2] : acc[0][0]);
                        const float v1 = (j & 2) ? ((j & 1) ? acc[3][2] : acc[3][0]) : ((j & 1) ? acc[2][2] : acc[2][0]);
                        st_rlx1(fin_dst, tagf(v0, tg));
                        st_rlx1(fin_dst + 32, tagf(v1, tg));
                        if (j == 0) st_rlx1(fin_dst + 64, tagf(acc[4][0], tg));
                        if (!dry) break;
                        dry = false;
#pragma unroll
                        for (int i = 0; i < 5; i++) { acc[i][0] = 0.f; acc[i][1] = 0.f; acc[i][2] = 0.f; acc[i][3] = 0.f; }
                        continue;
                    }
                    if (early) item = s_item[s];
                    release();
                    if (id == ID_WD) TRACE(6);
                } else if (id != ID_K) {
                    const int kq = warp >> 1;
                    const uint32_t a0 = sbase + s * STAGE_BYTES + (kq * 144 + l7 + (mi >> 1) * 8) * 64 +
                                        ((((warp & 1) * 2 + (mi & 1)) ^ (l7 >> 1)) << 4);
                    const uint32_t xa_ = sbase + OFF_XN + (kq * 144 + 2 * j) * 2;
                    uint32_t a[9][4], xf[18];
#pragma unroll
                    for (int ks = 0; ks < 9; ks++) {
                        ldsm4t(a[ks], a0 + ks * 1024);
                        xf[2 * ks] = lds32(xa_ + ks * 32); xf[2 * ks + 1] = lds32(xa_ + ks * 32 + 16);
                    }
                    float c0[4] = {0.f, 0.f, 0.f, 0.f}, c1[4] = {0.f, 0.f, 0.f, 0.f};
#pragma unroll
                    for (int ks = 0; ks < 9; ks++) mma16816((ks & 1) ? c1 : c0, a[ks], xf[2 * ks], xf[2 * ks + 1]);
                    float* red = reinterpret_cast<float*>(sptr + OFF_RED) + rb * 128;
                    if (j < 2) red[kq * 32 + (warp & 1) * 16 + j * 8 + g] = j ? c0[2] + c1[2] : c0[0] + c1[0];
                    release();
                    rb ^= 1;
                    cons_sync();
                    const float y = bf16r((red[lane] + red[32 + lane]) + (red[64 + lane] + red[96 + lane]));
                    if (id == ID_WQ && warp == 0) st_rlx1(&g_q[c * 32 + lane], tagf(y, tag));
                    const float sg = bf16r(ygate / (1.f + __expf(-ygate)));
                    reinterpret_cast<__nv_bfloat16*>(sptr + OFF_COEF)[warp * 32 + lane] = __float2bfloat16_rn(sg * y);
                    __syncwarp();
                    if (id == ID_WG) ygate = y;
                    if (id == ID_WQ) TRACE(2);
                }
                if (item & F_NEXT) known = ((item >> 24) & 63) << 16;
                if ((item & F_GATHER) || id == ID_K) {
                    TRACE(3);
                    uint32_t* q_s = reinterpret_cast<uint32_t*>(sptr + OFF_Q);
                    uint4 w[4];
#pragma unroll
                    for (int i = 0; i < 4; i++) { w[i].x = tag ^ 1u; w[i].y = w[i].z = w[i].w = tag; }
                    int it = 0;
                    bool all;
                    do {
                        all = true;
#pragma unroll
                        for (int i = 0; i < 4; i++)
                            if (!ok4(w[i], tag)) { w[i] = ld_rlx4(&g_q[(i * 256 + tid) * 4]); all = false; }
                    } while (!all && ++it < SPIN_LIMIT);
#pragma unroll
                    for (int i = 0; i < 4; i++) {
                        const int idx4 = i * 256 + tid, head = idx4 >> 5, dp = (idx4 & 31) * 2;
                        const int ks = dp >> 3, r = dp & 7;
                        const int pos = head * 64 + (r & 3) * 16 + ks * 2 + (r >> 2);
                        q_s[pos] = (w[i].x >> 16) | (w[i].y & 0xffff0000u);
                        q_s[pos + 16] = (w[i].z >> 16) | (w[i].w & 0xffff0000u);
                    }
                    cons_sync();
                    have_q = true;
                    TRACE(4);
                }
            }
            TRACE(8);
            TRACEV(10, nchunks);
        }
    }
}

typedef CUresult (*EncodeFn)(CUtensorMap*, CUtensorMapDataType, cuuint32_t, void*, const cuuint64_t*, const cuuint64_t*,
                             const cuuint32_t*, const cuuint32_t*, CUtensorMapInterleave, CUtensorMapSwizzle,
                             CUtensorMapL2promotion, CUtensorMapFloatOOBfill);

void make_map(EncodeFn enc, CUtensorMap* tm, const void* p, cuuint64_t d0, cuuint64_t d1, cuuint64_t d2,
              cuuint64_t s1, cuuint64_t s2, cuuint32_t b0, cuuint32_t b1, cuuint32_t b2, CUtensorMapSwizzle sw,
              CUtensorMapL2promotion promo = CU_TENSOR_MAP_L2_PROMOTION_L2_256B) {
    cuuint64_t gd[3] = {d0, d1, d2};
    cuuint64_t gs[2] = {s1, s2};
    cuuint32_t bx[3] = {b0, b1, b2};
    cuuint32_t es[3] = {1, 1, 1};
    enc(tm, CU_TENSOR_MAP_DATA_TYPE_BFLOAT16, 3, const_cast<void*>(p), gd, gs, bx, es, CU_TENSOR_MAP_INTERLEAVE_NONE,
        sw, promo, CU_TENSOR_MAP_FLOAT_OOB_FILL_NONE);
}

}

extern "C" void kernel_launch(void* const* d_in, const int* in_sizes, int n_in, void* d_out, int out_size) {
    (void)in_sizes; (void)n_in; (void)out_size;
    void* fn = nullptr;
    cudaDriverEntryPointQueryResult qr;
    cudaGetDriverEntryPoint("cuTensorMapEncodeTiled", &fn, cudaEnableDefault, &qr);
    EncodeFn enc = (EncodeFn)fn;
    int dev = 0, sms = 0;
    cudaGetDevice(&dev);
    cudaDeviceGetAttribute(&sms, cudaDevAttrMultiProcessorCount, dev);
    const int G = sms < MAXG ? sms : MAXG;
    cudaFuncSetAttribute(fused_decode_kernel, cudaFuncAttributeMaxDynamicSharedMemorySize, SMEM_BYTES);

    Params prm;
    make_map(enc, &prm.tm[ID_K], d_in[1], 64, (cuuint64_t)HKV * SK, 2, 256, 128, 64, 64, 2, CU_TENSOR_MAP_SWIZZLE_128B);
    make_map(enc, &prm.tm[ID_V], d_in[2], 64, (cuuint64_t)HKV * SK, 2, 256, 128, 64, 64, 2, CU_TENSOR_MAP_SWIZZLE_128B);
    make_map(enc, &prm.tm[ID_WQ], d_in[3], QW, 96, 6, QW * 2, QW * 2 * 96, 32, 96, 3, CU_TENSOR_MAP_SWIZZLE_64B);
    make_map(enc, &prm.tm[ID_WG], d_in[6], FF, 96, 6, FF * 2, FF * 2 * 96, 32, 96, 3, CU_TENSOR_MAP_SWIZZLE_64B);
    make_map(enc, &prm.tm[ID_WU], d_in[7], FF, 96, 6, FF * 2, FF * 2 * 96, 32, 96, 3, CU_TENSOR_MAP_SWIZZLE_64B, WU_PROMO);
    make_map(enc, &prm.tm[ID_WD], d_in[8], 64, FF, 9, DM * 2, 128, 64, 16, 9, CU_TENSOR_MAP_SWIZZLE_128B, W2_PROMO);
    make_map(enc, &prm.tm[ID_WO], d_in[4], 64, QW, 9, DM * 2, 128, 64, 16, 9, CU_TENSOR_MAP_SWIZZLE_128B, W2_PROMO);
    prm.x = (const __nv_bfloat16*)d_in[0];
    prm.out = (__nv_bfloat16*)d_out;
    fused_decode_kernel<<<G, NTHREADS, SMEM_BYTES>>>(prm);
}
```

```cpp
#include <cuda_runtime.h>
#include <cuda.h>
#include <cuda_bf16.h>
#include <stdint.h>

namespace {

constexpr int DM = 576, HKV = 16, SK = 16384, FF = 4608, QW = 4096;
constexpr int CHUNK = 128;
constexpr int CH_PER_HEAD = SK / CHUNK;
constexpr int NCHUNK = HKV * CH_PER_HEAD;
constexpr int NUNIT = FF / 32;
constexpr int HALF = 18432;
constexpr int KV_HALF = 64 * 256;
constexpr int STAGE_BYTES = 2 * HALF;
constexpr int NST = 5;
constexpr int KH_ATT = 4;
constexpr int KH_END = 6;
constexpr int KH_FILL = 2;
constexpr int CMB_MARGIN = 160;
constexpr int INIT_HEADS = 3;
constexpr int MAXG = 144;
constexpr int NTHREADS = 416;
constexpr int SPIN_LIMIT = 1 << 20;

enum { ID_K = 0, ID_V = 1, ID_WQ = 2, ID_WG = 3, ID_WU = 4, ID_WD = 5, ID_WO = 6 };
constexpr int F_GATHER = 1 << 20;
constexpr int F_LAST = 1 << 21;
constexpr int F_NEXT = 1 << 22;
constexpr int MAXLIST = 24;

constexpr int OFF_Q = NST * STAGE_BYTES;
constexpr int OFF_P = OFF_Q + 8192;
constexpr int OFF_RED = OFF_P + 512;
constexpr int OFF_XN = OFF_RED + 1024;
constexpr int OFF_X = OFF_XN + 1152;
constexpr int OFF_WMAX = OFF_X + 1152;
constexpr int OFF_WSUM = OFF_WMAX + 64;
constexpr int OFF_CMB = OFF_WSUM + 64;
constexpr int OFF_COEF = OFF_CMB + 576;
constexpr int OFF_LIST = OFF_COEF + 640;
constexpr int OFF_ITEM = OFF_LIST + MAXLIST * 4;
constexpr int OFF_BAR = OFF_ITEM + 32;
constexpr int SMEM_BYTES = OFF_BAR + (3 * NST + 4) * 8;

struct Params {
    CUtensorMap tm[7];
    const __nv_bfloat16* x;
    __nv_bfloat16* out;
};

__device__ __align__(128) float g_po[NCHUNK * 256];
__device__ __align__(128) float g_ml[NCHUNK * 8];
__device__ __align__(128) float g_q[QW];
__device__ __align__(128) float g_fin[MAXG * DM];
__device__ unsigned g_mark[MAXG];
__device__ unsigned g_epoch;
__device__ unsigned g_ctr;

__device__ __forceinline__ uint32_t smem_u32(const void* p) { return (uint32_t)__cvta_generic_to_shared(p); }
__device__ __forceinline__ void mbar_init(uint32_t bar, int cnt) {
    asm volatile("mbarrier.init.shared::cta.b64 [%0], %1;" ::"r"(bar), "r"(cnt) : "memory");
}
__device__ __forceinline__ void mbar_expect_tx(uint32_t bar, uint32_t bytes) {
    asm volatile("mbarrier.arrive.expect_tx.shared::cta.b64 _, [%0], %1;" ::"r"(bar), "r"(bytes) : "memory");
}
__device__ __forceinline__ void mbar_arrive(uint32_t bar) {
    asm volatile("mbarrier.arrive.shared::cta.b64 _, [%0];" ::"r"(bar) : "memory");
}
__device__ __forceinline__ void mbar_wait(uint32_t bar, uint32_t parity) {
    uint32_t ok;
    int it = 0;
    do {
        asm volatile(
            "{\n.reg .pred p;\n"
            "mbarrier.try_wait.parity.shared::cta.b64 p, [%1], %2;\n"
            "selp.u32 %0, 1, 0, p;\n}"
            : "=r"(ok) : "r"(bar), "r"(parity) : "memory");
    } while (!ok && ++it < SPIN_LIMIT);
}
__device__ __forceinline__ void tma3d(uint32_t dst, const CUtensorMap* tm, int c0, int c1, int c2, uint32_t bar, uint64_t pol) {
    asm volatile(
        "cp.async.bulk.tensor.3d.shared::cluster.global.mbarrier::complete_tx::bytes.L2::cache_hint [%0], [%1, {%3,%4,%5}], [%2], %6;"
        ::"r"(dst), "l"(tm), "r"(bar), "r"(c0), "r"(c1), "r"(c2), "l"(pol) : "memory");
}
__device__ __forceinline__ void cons_sync() { asm volatile("bar.sync 1, 256;" ::: "memory"); }
__device__ __forceinline__ void help_sync() { asm volatile("bar.sync 2, 128;" ::: "memory"); }

__device__ __forceinline__ uint32_t lds32(uint32_t a) {
    uint32_t v;
    asm volatile("ld.shared.u32 %0, [%1];" : "=r"(v) : "r"(a));
    return v;
}
__device__ __forceinline__ uint4 lds128(uint32_t a) {
    uint4 v;
    asm volatile("ld.shared.v4.u32 {%0,%1,%2,%3}, [%4];" : "=r"(v.x), "=r"(v.y), "=r"(v.z), "=r"(v.w) : "r"(a));
    return v;
}
__device__ __forceinline__ void ldsm4(uint32_t* r, uint32_t a) {
    asm volatile("ldmatrix.sync.aligned.m8n8.x4.shared.b16 {%0,%1,%2,%3}, [%4];"
                 : "=r"(r[0]), "=r"(r[1]), "=r"(r[2]), "=r"(r[3]) : "r"(a));
}
__device__ __forceinline__ void ldsm4t(uint32_t* r, uint32_t a) {
    asm volatile("ldmatrix.sync.aligned.m8n8.x4.trans.shared.b16 {%0,%1,%2,%3}, [%4];"
                 : "=r"(r[0]), "=r"(r[1]), "=r"(r[2]), "=r"(r[3]) : "r"(a));
}
__device__ __forceinline__ void mma16816(float* c, const uint32_t* a, uint32_t b0, uint32_t b1) {
    asm volatile(
        "mma.sync.aligned.m16n8k16.row.col.f32.bf16.bf16.f32 {%0,%1,%2,%3}, {%4,%5,%6,%7}, {%8,%9}, {%0,%1,%2,%3};"
        : "+f"(c[0]), "+f"(c[1]), "+f"(c[2]), "+f"(c[3])
        : "r"(a[0]), "r"(a[1]), "r"(a[2]), "r"(a[3]), "r"(b0), "r"(b1));
}
__device__ __forceinline__ uint4 ld_rlx4(const void* p) {
    uint4 v;
    asm volatile("ld.relaxed.gpu.global.v4.u32 {%0,%1,%2,%3}, [%4];"
                 : "=r"(v.x), "=r"(v.y), "=r"(v.z), "=r"(v.w) : "l"(p) : "memory");
    return v;
}
__device__ __forceinline__ uint2 ld_rlx2(const void* p) {
    uint2 v;
    asm volatile("ld.relaxed.gpu.global.v2.u32 {%0,%1}, [%2];" : "=r"(v.x), "=r"(v.y) : "l"(p) : "memory");
    return v;
}
__device__ __forceinline__ uint32_t ld_rlx1(const void* p) {
    uint32_t v;
    asm volatile("ld.relaxed.gpu.global.u32 %0, [%1];" : "=r"(v) : "l"(p) : "memory");
    return v;
}
__device__ __forceinline__ void st_rlx1(void* p, uint32_t v) {
    asm volatile("st.relaxed.gpu.global.u32 [%0], %1;" ::"l"(p), "r"(v) : "memory");
}
__device__ __forceinline__ void st_rlx2(void* p, uint32_t a, uint32_t b) {
    asm volatile("st.relaxed.gpu.global.v2.u32 [%0], {%1,%2};" ::"l"(p), "r"(a), "r"(b) : "memory");
}
__device__ __forceinline__ void st_rlx4(void* p, uint4 v) {
    asm volatile("st.relaxed.gpu.global.v4.u32 [%0], {%1,%2,%3,%4};" ::"l"(p), "r"(v.x), "r"(v.y), "r"(v.z), "r"(v.w) : "memory");
}
__device__ __forceinline__ uint32_t tagf(float v, uint32_t tag) { return (__float_as_uint(v) & ~1u) | tag; }
__device__ __forceinline__ float untag(uint32_t w) { return __uint_as_float(w & ~1u); }
__device__ __forceinline__ uint32_t mis2(uint32_t a, uint32_t b, uint32_t tag) {
    uint32_t r;
    asm("lop3.b32 %0, %1, %2, %3, 0x7e;" : "=r"(r) : "r"(a), "r"(b), "r"(tag));
    return r;
}
__device__ __forceinline__ bool ok4(uint4 v, uint32_t tag) { return ((mis2(v.x, v.y, tag) | mis2(v.z, v.w, tag)) & 1u) == 0u; }
__device__ __forceinline__ bool ok2(uint2 v, uint32_t tag) { return (mis2(v.x, v.y, tag) & 1u) == 0u; }
__device__ __forceinline__ float bf16r(float v) { return __bfloat162float(__float2bfloat16_rn(v)); }
__device__ __forceinline__ float blo(uint32_t w) { return __uint_as_float(w << 16); }
__device__ __forceinline__ float bhi(uint32_t w) { return __uint_as_float(w & 0xffff0000u); }
__device__ __forceinline__ float ex2(float v) { float r; asm("ex2.approx.ftz.f32 %0, %1;" : "=f"(r) : "f"(v)); return r; }
__device__ __forceinline__ float sum8(uint4 w) {
    return ((blo(w.x) + bhi(w.x)) + (blo(w.y) + bhi(w.y))) + ((blo(w.z) + bhi(w.z)) + (blo(w.w) + bhi(w.w)));
}
__device__ __forceinline__ float sq8(uint4 w, float m) {
    float a, s = 0.f;
    a = blo(w.x) - m; s = fmaf(a, a, s); a = bhi(w.x) - m; s = fmaf(a, a, s);
    a = blo(w.y) - m; s = fmaf(a, a, s); a = bhi(w.y) - m; s = fmaf(a, a, s);
    a = blo(w.z) - m; s = fmaf(a, a, s); a = bhi(w.z) - m; s = fmaf(a, a, s);
    a = blo(w.w) - m; s = fmaf(a, a, s); a = bhi(w.w) - m; s = fmaf(a, a, s);
    return s;
}
__device__ __forceinline__ uint32_t pack_bf16(float lo, float hi) {
    return (__float_as_uint(lo) >> 16) | (__float_as_uint(hi) & 0xffff0000u);
}

constexpr float LOG2E = 1.4426950408889634f;

__global__ void __launch_bounds__(NTHREADS, 1)
fused_decode_kernel(const __grid_constant__ Params prm) {
    extern __shared__ __align__(1024) uint8_t sptr[];
    const uint32_t sbase = smem_u32(sptr);
    const int tid = threadIdx.x, warp = tid >> 5, lane = tid & 31;
    const int b = blockIdx.x, G = gridDim.x;
    const uint32_t bar_full = sbase + OFF_BAR;
    const uint32_t bar_empty = bar_full + 2 * NST * 8;
    const uint32_t bar_go = bar_empty + NST * 8, bar_o = bar_go + 8, bar_tail = bar_o + 8, bar_mark = bar_tail + 8;
    volatile int* s_item = reinterpret_cast<volatile int*>(sptr + OFF_ITEM);

    if (warp == 8) {
        uint64_t pol_s, pol_n;
        asm volatile("createpolicy.fractional.L2::evict_first.b64 %0, 1.0;" : "=l"(pol_s));
        asm volatile("createpolicy.fractional.L2::evict_normal.b64 %0, 1.0;" : "=l"(pol_n));
        const int u0 = 2 * G - 1 - b;
        const int pro = (G >= 128 && (b < 128 || u0 < NUNIT)) ? 2 : 0;
        int* list = reinterpret_cast<int*>(sptr + OFF_LIST);
        int npre = 0, nall = 0;
        if (lane == 0) {
            const int uf = u0 < NUNIT ? u0 : b;
#pragma unroll
            for (int i = 0; i < 4; i++) mbar_init(bar_full + i * 8, 1);
            if (pro) {
#pragma unroll
                for (int i = 0; i < 4; i++) {
                    const CUtensorMap* tm = &prm.tm[(b < 128 ? ID_WQ : ID_WG) + (i >> 1)];
                    mbar_expect_tx(bar_full + i * 8, HALF);
                    tma3d(sbase + i * HALF, tm, ((i < 2 && b < 128) ? b : uf) * 32, 0, (i & 1) * 3, bar_full + i * 8, pol_n);
                }
            }
            for (int i = 4; i < 2 * NST; i++) mbar_init(bar_full + i * 8, 1);
            for (int i = 0; i < NST; i++) mbar_init(bar_empty + i * 8, 8);
            for (int i = 0; i < 4; i++) mbar_init(bar_go + i * 8, 1);
            int n = 0;
#pragma unroll 1
            for (int t = b; t < 128; t += G) list[n++] = ID_WQ << 16 | t;
#pragma unroll 1
            for (int u = u0; u < NUNIT; u += G) {
                list[n++] = ID_WG << 16 | u; list[n++] = ID_WU << 16 | u; list[n++] = ID_WD << 16 | u;
            }
            list[n++] = ID_WG << 16 | b | F_GATHER;
            npre = n;
            list[n++] = ID_WU << 16 | b;
            list[n++] = ID_WD << 16 | b;
#pragma unroll 1
            for (int t = b; t < 128; t += G) list[n++] = ID_WO << 16 | t;
            list[n - 1] |= F_LAST;
#pragma unroll 1
            for (int i = npre; i + 1 < n; i++) list[i] |= F_NEXT | ((list[i + 1] >> 16) & 63) << 24;
            nall = n;
            s_item[0] = list[0];
            s_item[1] = list[1];
            s_item[NST] = -1;
            asm volatile("fence.mbarrier_init.release.cluster;" ::: "memory");
        }
        __syncwarp();
        asm volatile("bar.arrive 3, %0;" ::"n"(NTHREADS) : "memory");
        if (lane == 0) {
            int s = pro; uint32_t ph = 1;
            int infl = 2 * pro;
            int lh = 0; uint32_t lph = 0;
            int li = pro;
            int c = b, nxt = 0;
            bool isv = false;
#pragma unroll 1
            while (li < nall) {
                int item, limit = (c >= NCHUNK - G) ? KH_END : KH_ATT;
                if (li == npre && c < NCHUNK) {
                    item = (isv ? ID_V << 16 : ID_K << 16) | c;
                } else {
                    item = list[li];
                    if (li >= npre) limit = KH_FILL;
                    li++;
                }
                const int id = (item >> 16) & 7, t = item & 0xffff;
                const bool col = id >= ID_WQ && id <= ID_WU;
                const int c0 = col ? t * 32 : 0;
                const int c1 = col ? 0 : (id <= ID_V ? t * CHUNK : (id == ID_WD ? t * 32 : (t >> 3) * 256 + (t & 7) * 16));
                const int d1 = col ? 0 : (id <= ID_V ? 64 : (id == ID_WD ? 16 : 128));
                const uint32_t bytes = id <= ID_V ? KV_HALF : HALF;
                mbar_wait(bar_empty + s * 8, ph);
                s_item[s] = item;
#pragma unroll 1
                for (int h = 0; h < 2; h++) {
                    while (infl >= limit) {
                        mbar_wait(bar_full + lh * 8, lph);
                        if (++lh == 2 * NST) { lh = 0; lph ^= 1; }
                        infl--;
                    }
                    infl++;
                    const uint32_t fb = bar_full + (s * 2 + h) * 8;
                    mbar_expect_tx(fb, bytes);
                    tma3d(sbase + s * STAGE_BYTES + h * HALF, &prm.tm[id], c0, c1 + h * d1, col ? 3 * h : 0, fb,
                          col ? pol_n : pol_s);
                }
                if (++s == NST) { s = 0; ph ^= 1; }
                if (id == ID_K) {
                    nxt = G + (int)atomicInc(&g_ctr, NCHUNK - 1);
                    isv = true;
                } else if (id == ID_V) {
                    if (nxt >= NCHUNK) s_item[NST] = c;
                    c = nxt;
                    isv = false;
                }
            }
            while (infl > 0) {
                mbar_wait(bar_full + lh * 8, lph);
                if (++lh == 2 * NST) { lh = 0; lph ^= 1; }
                infl--;
            }
            mbar_arrive(bar_tail);
        }
    } else {
        uint4 xa, xb, xc;
        uint32_t xmine = 0, xmine2 = 0;
        if (warp < 8) {
            const uint4* x4 = reinterpret_cast<const uint4*>(prm.x);
            xa = __ldg(x4 + lane); xb = __ldg(x4 + 32 + lane);
            xc = make_uint4(0, 0, 0, 0);
            if (lane < 8) xc = __ldg(x4 + 64 + lane);
            xmine = __ldg(reinterpret_cast<const uint32_t*>(prm.x) + tid);
            if (tid < 32) xmine2 = __ldg(reinterpret_cast<const uint32_t*>(prm.x) + 256 + tid);
        }
        const uint32_t epoch = ld_rlx1(&g_epoch);
        asm volatile("bar.sync 3, %0;" ::"n"(NTHREADS) : "memory");
        const uint32_t tag = (epoch + 1u) & 1u;
        if (warp > 8) {
            const int hw = warp - 9;
            float* cmb = reinterpret_cast<float*>(sptr + OFF_CMB);
            __nv_bfloat16* o_s = reinterpret_cast<__nv_bfloat16*>(sptr + OFF_COEF + 512);
            {
                const uint32_t inv = tag ^ 1u;
                const uint4 iv = make_uint4(inv, inv, inv, inv);
                constexpr int c_lo = (HKV - INIT_HEADS) * CH_PER_HEAD, n_o = INIT_HEADS * CH_PER_HEAD * 64;
#pragma unroll 1
                for (int i = b * 128 + (tid - 288); i < n_o + n_o / 32; i += G * 128)
                    st_rlx4(i < n_o ? g_po + c_lo * 256 + i * 4 : g_ml + c_lo * 8 + (i - n_o) * 4, iv);
            }
#pragma unroll 1
            for (int pass = 0; pass < 2; pass++) {
                const uint32_t miss = tag ^ pass;
                if (pass && b < 128) mbar_wait(bar_go, 0);
                int ti = 0;
#pragma unroll 1
                for (int t = pass ? b : 127; t < 128; t += G, ti++) {
                    const int c4 = lane & 7, ri = lane >> 3;
                    const int cr = (t >> 3) * CH_PER_HEAD + hw * 32 + ri;
                    const float* po = g_po + (size_t)cr * 256 + (t & 7) * 32 + c4 * 4;
                    const float* pm = g_ml + cr * 8 + (c4 >> 2) * 2;
                    uint4 o4[8]; uint2 ml[8];
#pragma unroll
                    for (int i = 0; i < 8; i++) { o4[i] = make_uint4(miss, tag, tag, tag); ml[i] = make_uint2(miss, tag); }
                    int it = 0;
                    bool all;
                    do {
                        all = true;
#pragma unroll
                        for (int i = 0; i < 8; i++) {
                            if (!ok4(o4[i], tag)) { o4[i] = ld_rlx4(po + i * 1024); all = false; }
                            if (!ok2(ml[i], tag)) { ml[i] = ld_rlx2(pm + i * 32); all = false; }
                        }
                    } while (!all && ++it < SPIN_LIMIT);
                    float mw = untag(ml[0].x);
#pragma unroll
                    for (int i = 1; i < 8; i++) mw = fmaxf(mw, untag(ml[i].x));
                    mw = fmaxf(mw, __shfl_xor_sync(~0u, mw, 8));
                    mw = fmaxf(mw, __shfl_xor_sync(~0u, mw, 16));
                    float ox = 0.f, oy = 0.f, oz = 0.f, ow = 0.f, lw = 0.f;
#pragma unroll
                    for (int i = 0; i < 8; i++) {
                        const float f = ex2((untag(ml[i].x) - mw) * LOG2E);
                        ox = fmaf(f, untag(o4[i].x), ox); oy = fmaf(f, untag(o4[i].y), oy);
                        oz = fmaf(f, untag(o4[i].z), oz); ow = fmaf(f, untag(o4[i].w), ow);
                        lw = fmaf(f, untag(ml[i].y), lw);
                    }
#pragma unroll
                    for (int o = 8; o <= 16; o <<= 1) {
                        ox += __shfl_xor_sync(~0u, ox, o); oy += __shfl_xor_sync(~0u, oy, o);
                        oz += __shfl_xor_sync(~0u, oz, o); ow += __shfl_xor_sync(~0u, ow, o);
                        lw += __shfl_xor_sync(~0u, lw, o);
                    }
                    if (ti) help_sync();
                    if (lane < 8) *reinterpret_cast<float4*>(cmb + hw * 36 + lane * 4) = make_float4(ox, oy, oz, ow);
                    if (lane == 0 || lane == 4) { cmb[hw * 36 + 32 + (lane >> 1)] = mw; cmb[hw * 36 + 33 + (lane >> 1)] = lw; }
                    help_sync();
                    if (hw == 0) {
                        const float* mlp = cmb + 32 + (lane >> 4) * 2;
                        const float M = fmaxf(fmaxf(mlp[0], mlp[36]), fmaxf(mlp[72], mlp[108]));
                        float on = 0.f, L = 0.f;
#pragma unroll
                        for (int w = 0; w < 4; w++) {
                            const float f = ex2((mlp[w * 36] - M) * LOG2E);
                            on = fmaf(f, cmb[w * 36 + lane], on);
                            L = fmaf(f, mlp[w * 36 + 1], L);
                        }
                        o_s[(ti & 1) * 32 + (lane & 16) + ((lane & 15) >> 1) + (lane & 1) * 8] = __float2bfloat16_rn(on / L);
                    }
                }
                if (hw == 0) {
                    __syncwarp();
                    if (lane == 0 && pass) mbar_arrive(bar_o);
                } else if (hw == 3) {
                    if (pass == 0) {
                        if (lane == 0) { __threadfence(); st_rlx1(&g_mark[b], tag); }
                        __nanosleep(8000);
#pragma unroll 1
                        for (int i = lane; i < G; i += 32) {
                            int it = 0;
                            while (((ld_rlx1(&g_mark[i]) ^ tag) & 1u) && ++it < SPIN_LIMIT) __nanosleep(500);
                        }
                        __threadfence();
                        __syncwarp();
                        if (lane == 0) mbar_arrive(bar_mark);
                    }
                } else {
                    int k = pass ? b + (hw - 1) * G : 143;
                    if (pass && k < 144) mbar_wait(bar_tail, 0);
#pragma unroll 1
                    for (; k < 144; k += 2 * G) {
                        const float* src = &g_fin[lane * DM + k * 4];
                        uint4 w[5];
#pragma unroll
                        for (int i = 0; i < 5; i++) w[i] = make_uint4(lane + 32 * i < G ? miss : tag, tag, tag, tag);
                        int it = 0;
                        bool all;
                        do {
                            all = true;
#pragma unroll
                            for (int i = 0; i < 5; i++)
                                if (!ok4(w[i], tag)) { w[i] = ld_rlx4(src + i * 32 * DM); all = false; }
                            all = __all_sync(~0u, all);
                        } while (!all && ++it < SPIN_LIMIT);
                        float sx = 0.f, sy = 0.f, sz = 0.f, sw = 0.f;
#pragma unroll
                        for (int i = 0; i < 5; i++) { sx += untag(w[i].x); sy += untag(w[i].y); sz += untag(w[i].z); sw += untag(w[i].w); }
                        const bool b4 = lane & 16, b3 = lane & 8;
                        const float r0 = (b4 ? sz : sx) + __shfl_xor_sync(~0u, b4 ? sx : sz, 16);
                        const float r1 = (b4 ? sw : sy) + __shfl_xor_sync(~0u, b4 ? sy : sw, 16);
                        float r = (b3 ? r1 : r0) + __shfl_xor_sync(~0u, b3 ? r0 : r1, 8);
                        r += __shfl_xor_sync(~0u, r, 4);
                        r += __shfl_xor_sync(~0u, r, 2);
                        r += __shfl_xor_sync(~0u, r, 1);
                        const int col = k * 4 + (lane >> 3);
                        const float xv = __bfloat162float(reinterpret_cast<const __nv_bfloat16*>(sptr + OFF_X)[col]);
                        if ((lane & 7) == 0 && pass) prm.out[col] = __float2bfloat16_rn(xv + r);
                        if (k == 0 && lane == 0) st_rlx1(&g_epoch, epoch + 1u);
                    }
                }
                if (pass == 0) help_sync();
            }
        } else {
            const int g = lane >> 2, j = lane & 3;
            const int mi = lane >> 3, l7 = lane & 7;
            float* const fin_dst = &g_fin[b * DM + warp * 72 + j * 8 + g];
            {
                float s = sum8(xa) + sum8(xb) + sum8(xc);
#pragma unroll
                for (int o = 16; o; o >>= 1) s += __shfl_xor_sync(~0u, s, o);
                const float mean = s * (1.f / DM);
                float v = sq8(xa, mean) + sq8(xb, mean) + (lane < 8 ? sq8(xc, mean) : 0.f);
#pragma unroll
                for (int o = 16; o; o >>= 1) v += __shfl_xor_sync(~0u, v, o);
                const float mb = bf16r(mean);
                const float sd = bf16r(sqrtf(bf16r(bf16r(v * (1.f / DM)) + 1e-5f)));
                uint32_t* xn_s = reinterpret_cast<uint32_t*>(sptr + OFF_XN);
                xn_s[tid] = pack_bf16(bf16r(bf16r(blo(xmine) - mb) / sd), bf16r(bf16r(bhi(xmine) - mb) / sd));
                xn_s[288 + tid] = xmine;
                if (tid < 32) {
                    xn_s[256 + tid] = pack_bf16(bf16r(bf16r(blo(xmine2) - mb) / sd), bf16r(bf16r(bhi(xmine2) - mb) / sd));
                    xn_s[288 + 256 + tid] = xmine2;
                }
                cons_sync();
            }

            int s = 0; uint32_t ph = 0;
            int rb = 0;
            float acc[5][4];
#pragma unroll
            for (int i = 0; i < 5; i++) { acc[i][0] = 0.f; acc[i][1] = 0.f; acc[i][2] = 0.f; acc[i][3] = 0.f; }
            auto release = [&]() {
                __syncwarp();
                if (lane == 0) mbar_arrive(bar_empty + s * 8);
                if (++s == NST) { s = 0; ph ^= 1; }
            };
            float* wmax = reinterpret_cast<float*>(sptr + OFF_WMAX);
            float* wsum = reinterpret_cast<float*>(sptr + OFF_WSUM);
            __nv_bfloat16* p_s = reinterpret_cast<__nv_bfloat16*>(sptr + OFF_P);
            const bool bl = (g == 0) || (g == 2);
            const uint32_t k_off = (warp >> 2) * HALF + (16 * (warp & 3) + l7 + (mi & 1) * 8) * 128;
            const uint32_t k_x = ((mi >> 1) ^ l7) << 4;
            const int vchunk = 2 * warp + (mi & 1);
            const uint32_t v_off = (vchunk >> 3) * 8192 + (l7 + (mi >> 1) * 8) * 128 + (((vchunk & 7) ^ l7) << 4);
            const uint32_t q_addr = sbase + OFF_Q + ((g >> 1) * 64 + j * 16) * 4;
            const uint32_t p_addr = sbase + OFF_P + (g >> 1) * 256 + j * 64;
            int tl = b;
            while (tl + G < 128) tl += G;
            const int go_thr = ((tl >> 3) + 1) * CH_PER_HEAD + CMB_MARGIN;
            bool fired = false;
            int nwo = 0;
            float ygate = 0.f;

            bool dry = true;
            int known = ID_WD << 16 | F_LAST;
#pragma unroll 1
            while (true) {
                const bool early = ((known >> 16) & 7) >= ID_WD;
                if (!early) mbar_wait(bar_full + (s * 2 + (warp >> 2)) * 8, ph);
                int item = early ? known : s_item[s];
                known = 0;
                const int id = (item >> 16) & 7, c = item & 0xffff;
                if (id == ID_K) {
                    if (c >= (HKV - INIT_HEADS) * CH_PER_HEAD) mbar_wait(bar_mark, 0);
                    uint32_t bf[16];
                    if (bl) {
#pragma unroll
                        for (int i = 0; i < 4; i++) {
                            const uint4 v = lds128(q_addr + (c >> 7) * 512 + i * 16);
                            bf[i * 4] = v.x; bf[i * 4 + 1] = v.y; bf[i * 4 + 2] = v.z; bf[i * 4 + 3] = v.w;
                        }
                    } else {
#pragma unroll
                        for (int i = 0; i < 16; i++) bf[i] = 0u;
                    }
                    uint32_t a[8][4];
                    {
                        const uint32_t kb = sbase + s * STAGE_BYTES + k_off;
#pragma unroll
                        for (int ks = 0; ks < 8; ks++) ldsm4(a[ks], kb + (ks >> 2) * 8192 + (k_x ^ ((ks & 3) << 5)));
                    }
                    float c0[4] = {0.f, 0.f, 0.f, 0.f}, c1[4] = {0.f, 0.f, 0.f, 0.f};
#pragma unroll
                    for (int ks = 0; ks < 8; ks += 2) {
                        mma16816(c0, a[ks], bf[2 * ks], bf[2 * ks + 1]);
                        mma16816(c1, a[ks + 1], bf[2 * ks + 2], bf[2 * ks + 3]);
                    }
                    release();
                    const float sa = bf16r(bf16r(c0[0] + c1[0]) * 0.08838834764831845f);
                    const float sb = bf16r(bf16r(c0[2] + c1[2]) * 0.08838834764831845f);
                    float mx = fmaxf(sa, sb);
                    mx = fmaxf(mx, __shfl_xor_sync(~0u, mx, 4));
                    mx = fmaxf(mx, __shfl_xor_sync(~0u, mx, 8));
                    mx = fmaxf(mx, __shfl_xor_sync(~0u, mx, 16));
                    if (lane < 2) wmax[lane * 8 + warp] = mx;
                    cons_sync();
                    float m;
                    {
                        const float4 u = *reinterpret_cast<const float4*>(wmax + (j & 1) * 8);
                        const float4 v = *reinterpret_cast<const float4*>(wmax + (j & 1) * 8 + 4);
                        m = fmaxf(fmaxf(fmaxf(u.x, u.y), fmaxf(u.z, u.w)), fmaxf(fmaxf(v.x, v.y), fmaxf(v.z, v.w)));
                    }
                    const float ea = ex2((sa - m) * LOG2E), eb = ex2((sb - m) * LOG2E);
                    if (j < 2) {
                        const int pos = j * 128 + (g >> 1) * 32 + warp * 4 + (g & 1);
                        p_s[pos] = __float2bfloat16_rn(ea);
                        p_s[pos + 2] = __float2bfloat16_rn(eb);
                    }
                    float es = ea + eb;
                    es += __shfl_xor_sync(~0u, es, 4);
                    es += __shfl_xor_sync(~0u, es, 8);
                    es += __shfl_xor_sync(~0u, es, 16);
                    if (lane < 2) wsum[lane * 8 + warp] = es;
                    cons_sync();
                    if (bl) {
#pragma unroll
                        for (int i = 0; i < 4; i++) {
                            const uint4 v = lds128(p_addr + i * 16);
                            bf[i * 4] = v.x; bf[i * 4 + 1] = v.y; bf[i * 4 + 2] = v.z; bf[i * 4 + 3] = v.w;
                        }
                    }
                    if (warp == (c & 7)) {
                        const int hh = (lane >> 1) & 1;
                        const float mh = __shfl_sync(~0u, m, hh);
                        const float4 u = *reinterpret_cast<const float4*>(wsum + hh * 8);
                        const float4 v = *reinterpret_cast<const float4*>(wsum + hh * 8 + 4);
                        const float l = ((u.x + u.y) + (u.z + u.w)) + ((v.x + v.y) + (v.z + v.w));
                        if (lane < 8) st_rlx1(g_ml + c * 8 + lane, tagf((lane & 1) ? l : mh, tag));
                    }
#pragma unroll
                    for (int k = 0; k < 4; k++) { c0[k] = 0.f; c1[k] = 0.f; }
#pragma unroll
                    for (int h = 0; h < 2; h++) {
                        mbar_wait(bar_full + (s * 2 + h) * 8, ph);
                        const uint32_t vb = sbase + s * STAGE_BYTES + h * HALF + v_off;
#pragma unroll
                        for (int ks = 0; ks < 4; ks++) ldsm4t(a[ks], vb + ks * 2048);
                        mma16816(c0, a[0], bf[8 * h], bf[8 * h + 1]);
                        mma16816(c1, a[1], bf[8 * h + 2], bf[8 * h + 3]);
                        mma16816(c0, a[2], bf[8 * h + 4], bf[8 * h + 5]);
                        mma16816(c1, a[3], bf[8 * h + 6], bf[8 * h + 7]);
                    }
                    if (j < 2)
                        st_rlx2(g_po + (size_t)c * 256 + warp * 32 + j * 16 + g * 2,
                                tagf(c0[0] + c1[0], tag), tagf(c0[2] + c1[2], tag));
                    release();
                    if (tid == 0 && !fired && (c >= go_thr || c == s_item[NST])) { mbar_arrive(bar_go); fired = true; }
                    continue;
                }
                if (id >= ID_WD) {
                    if (id == ID_WO && tid == 0 && !fired) { mbar_arrive(bar_go); fired = true; }
                    uint32_t ca = sbase + OFF_COEF + warp * 64 + j * 4;
                    if (id == ID_WO) {
                        mbar_wait(bar_o, 0);
                        ca = sbase + OFF_COEF + 512 + (nwo & 1) * 64 + j * 4;
                        nwo++;
                    }
                    const uint32_t a0 = sbase + s * STAGE_BYTES + (l7 + (mi >> 1) * 8) * 128;
#pragma unroll 1
                    for (int h = 0; h < 2; h++) {
                        const uint32_t b0 = lds32(ca + h * 32), b1 = lds32(ca + h * 32 + 16);
                        if (!dry) mbar_wait(bar_full + (s * 2 + h) * 8, ph);
                        uint32_t a[5][4];
#pragma unroll
                        for (int i = 0; i < 5; i++) {
                            const int ch = warp * 9 + (i < 4 ? 2 * i + (mi & 1) : 8);
                            ldsm4t(a[i], a0 + h * HALF + (ch >> 3) * 2048 + (((ch & 7) ^ l7) << 4));
                        }
#pragma unroll
                        for (int i = 0; i < 5; i++) mma16816(acc[i], a[i], b0, b1);
                    }
                    if (item & F_LAST) {
                        const uint32_t tg = dry ? tag ^ 1u : tag;
                        const float v0 = (j & 2) ? ((j & 1) ? acc[1][2] : acc[1][0]) : ((j & 1) ? acc[0][2] : acc[0][0]);
                        const float v1 = (j & 2) ? ((j & 1) ? acc[3][2] : acc[3][0]) : ((j & 1) ? acc[2][2] : acc[2][0]);
                        st_rlx1(fin_dst, tagf(v0, tg));
                        st_rlx1(fin_dst + 32, tagf(v1, tg));
                        if (j == 0) st_rlx1(fin_dst + 64, tagf(acc[4][0], tg));
                        if (!dry) break;
                        dry = false;
#pragma unroll
                        for (int i = 0; i < 5; i++) { acc[i][0] = 0.f; acc[i][1] = 0.f; acc[i][2] = 0.f; acc[i][3] = 0.f; }
                        continue;
                    }
                    if (early) item = s_item[s];
                    release();
                } else {
                    const int kq = warp >> 1;
                    const uint32_t a0 = sbase + s * STAGE_BYTES + (kq * 144 + l7 + (mi >> 1) * 8) * 64 +
                                        ((((warp & 1) * 2 + (mi & 1)) ^ (l7 >> 1)) << 4);
                    const uint32_t xa_ = sbase + OFF_XN + (kq * 144 + 2 * j) * 2;
                    uint32_t a[9][4], xf[18];
#pragma unroll
                    for (int ks = 0; ks < 9; ks++) {
                        ldsm4t(a[ks], a0 + ks * 1024);
                        xf[2 * ks] = lds32(xa_ + ks * 32); xf[2 * ks + 1] = lds32(xa_ + ks * 32 + 16);
                    }
                    float c0[4] = {0.f, 0.f, 0.f, 0.f}, c1[4] = {0.f, 0.f, 0.f, 0.f};
#pragma unroll
                    for (int ks = 0; ks < 9; ks++) mma16816((ks & 1) ? c1 : c0, a[ks], xf[2 * ks], xf[2 * ks + 1]);
                    float* red = reinterpret_cast<float*>(sptr + OFF_RED) + rb * 128;
                    if (j < 2) red[kq * 32 + (warp & 1) * 16 + j * 8 + g] = j ? c0[2] + c1[2] : c0[0] + c1[0];
                    release();
                    rb ^= 1;
                    cons_sync();
                    const float y = bf16r((red[lane] + red[32 + lane]) + (red[64 + lane] + red[96 + lane]));
                    if (id == ID_WQ && warp == 0) st_rlx1(&g_q[c * 32 + lane], tagf(y, tag));
                    const float sg = bf16r(ygate / (1.f + __expf(-ygate)));
                    reinterpret_cast<__nv_bfloat16*>(sptr + OFF_COEF)[warp * 32 + lane] = __float2bfloat16_rn(sg * y);
                    __syncwarp();
                    if (id == ID_WG) ygate = y;
                }
                if (item & F_NEXT) known = ((item >> 24) & 63) << 16;
                if (item & F_GATHER) {
                    uint32_t* q_s = reinterpret_cast<uint32_t*>(sptr + OFF_Q);
                    uint4 w[4];
#pragma unroll
                    for (int i = 0; i < 4; i++) { w[i].x = tag ^ 1u; w[i].y = w[i].z = w[i].w = tag; }
                    int it = 0;
                    bool all;
                    do {
                        all = true;
#pragma unroll
                        for (int i = 0; i < 4; i++)
                            if (!ok4(w[i], tag)) { w[i] = ld_rlx4(&g_q[(i * 256 + tid) * 4]); all = false; }
                    } while (!all && ++it < SPIN_LIMIT);
#pragma unroll
                    for (int i = 0; i < 4; i++) {
                        const int idx4 = i * 256 + tid, head = idx4 >> 5, dp = (idx4 & 31) * 2;
                        const int ks = dp >> 3, r = dp & 7;
                        const int pos = head * 64 + (r & 3) * 16 + ks * 2 + (r >> 2);
                        q_s[pos] = (w[i].x >> 16) | (w[i].y & 0xffff0000u);
                        q_s[pos + 16] = (w[i].z >> 16) | (w[i].w & 0xffff0000u);
                    }
                    cons_sync();
                }
            }
        }
    }
}

typedef CUresult (*EncodeFn)(CUtensorMap*, CUtensorMapDataType, cuuint32_t, void*, const cuuint64_t*, const cuuint64_t*,
                             const cuuint32_t*, const cuuint32_t*, CUtensorMapInterleave, CUtensorMapSwizzle,
                             CUtensorMapL2promotion, CUtensorMapFloatOOBfill);

void make_map(EncodeFn enc, CUtensorMap* tm, const void* p, cuuint64_t d0, cuuint64_t d1, cuuint64_t d2,
              cuuint64_t s1, cuuint64_t s2, cuuint32_t b0, cuuint32_t b1, cuuint32_t b2, CUtensorMapSwizzle sw) {
    cuuint64_t gd[3] = {d0, d1, d2};
    cuuint64_t gs[2] = {s1, s2};
    cuuint32_t bx[3] = {b0, b1, b2};
    cuuint32_t es[3] = {1, 1, 1};
    enc(tm, CU_TENSOR_MAP_DATA_TYPE_BFLOAT16, 3, const_cast<void*>(p), gd, gs, bx, es, CU_TENSOR_MAP_INTERLEAVE_NONE,
        sw, CU_TENSOR_MAP_L2_PROMOTION_L2_256B, CU_TENSOR_MAP_FLOAT_OOB_FILL_NONE);
}

}

extern "C" void kernel_launch(void* const* d_in, const int* in_sizes, int n_in, void* d_out, int out_size) {
    (void)in_sizes; (void)n_in; (void)out_size;
    void* fn = nullptr;
    cudaDriverEntryPointQueryResult qr;
    cudaGetDriverEntryPoint("cuTensorMapEncodeTiled", &fn, cudaEnableDefault, &qr);
    EncodeFn enc = (EncodeFn)fn;
    int dev = 0, sms = 0;
    cudaGetDevice(&dev);
    cudaDeviceGetAttribute(&sms, cudaDevAttrMultiProcessorCount, dev);
    const int G = sms < MAXG ? sms : MAXG;
    cudaFuncSetAttribute(fused_decode_kernel, cudaFuncAttributeMaxDynamicSharedMemorySize, SMEM_BYTES);

    Params prm;
    make_map(enc, &prm.tm[ID_K], d_in[1], 64, (cuuint64_t)HKV * SK, 2, 256, 128, 64, 64, 2, CU_TENSOR_MAP_SWIZZLE_128B);
    make_map(enc, &prm.tm[ID_V], d_in[2], 64, (cuuint64_t)HKV * SK, 2, 256, 128, 64, 64, 2, CU_TENSOR_MAP_SWIZZLE_128B);
    make_map(enc, &prm.tm[ID_WQ], d_in[3], QW, 96, 6, QW * 2, QW * 2 * 96, 32, 96, 3, CU_TENSOR_MAP_SWIZZLE_64B);
    make_map(enc, &prm.tm[ID_WG], d_in[6], FF, 96, 6, FF * 2, FF * 2 * 96, 32, 96, 3, CU_TENSOR_MAP_SWIZZLE_64B);
    make_map(enc, &prm.tm[ID_WU], d_in[7], FF, 96, 6, FF * 2, FF * 2 * 96, 32, 96, 3, CU_TENSOR_MAP_SWIZZLE_64B);
    make_map(enc, &prm.tm[ID_WD], d_in[8], 64, FF, 9, DM * 2, 128, 64, 16, 9, CU_TENSOR_MAP_SWIZZLE_128B);
    make_map(enc, &prm.tm[ID_WO], d_in[4], 64, QW, 9, DM * 2, 128, 64, 16, 9, CU_TENSOR_MAP_SWIZZLE_128B);
    prm.x = (const __nv_bfloat16*)d_in[0];
    prm.out = (__nv_bfloat16*)d_out;
    fused_decode_kernel<<<G, NTHREADS, SMEM_BYTES>>>(prm);
}
```

```cpp
#include <cuda_runtime.h>
#include <cuda.h>
#include <cuda_bf16.h>
#include <stdint.h>

namespace {

constexpr int DM = 576, HKV = 16, SK = 16384, FF = 4608, QW = 4096;
constexpr int CHUNK = 128;
constexpr int CH_PER_HEAD = SK / CHUNK;
constexpr int NCHUNK = HKV * CH_PER_HEAD;
constexpr int NUNIT = FF / 32;
constexpr int HALF = 18432;
constexpr int KV_HALF = 64 * 256;
constexpr int STAGE_BYTES = 2 * HALF;
constexpr int NST = 5;
constexpr int KH_ATT = 4;
constexpr int KH_END = 6;
constexpr int KH_FILL = 2;
constexpr int CMB_MARGIN = 160;
constexpr int INIT_HEADS = 3;
constexpr int MAXG = 144;
constexpr int NTHREADS = 416;
constexpr uint32_t WAIT_LIMIT = 1u << 30;

enum { ID_K = 0, ID_V = 1, ID_WQ = 2, ID_WG = 3, ID_WU = 4, ID_WD = 5, ID_WO = 6 };
constexpr int F_GATHER = 1 << 20;
constexpr int F_LAST = 1 << 21;
constexpr int F_NEXT = 1 << 22;
constexpr int MAXLIST = 24;

constexpr int OFF_Q = NST * STAGE_BYTES;
constexpr int OFF_P = OFF_Q + 8192;
constexpr int OFF_RED = OFF_P + 512;
constexpr int OFF_XN = OFF_RED + 1024;
constexpr int OFF_X = OFF_XN + 1152;
constexpr int OFF_WMAX = OFF_X + 1152;
constexpr int OFF_WSUM = OFF_WMAX + 64;
constexpr int OFF_CMB = OFF_WSUM + 64;
constexpr int OFF_COEF = OFF_CMB + 576;
constexpr int OFF_LIST = OFF_COEF + 640;
constexpr int OFF_ITEM = OFF_LIST + MAXLIST * 4;
constexpr int OFF_BAR = OFF_ITEM + 32;
constexpr int SMEM_BYTES = OFF_BAR + (3 * NST + 4) * 8;

struct Params {
    CUtensorMap tm[7];
    const __nv_bfloat16* x;
    __nv_bfloat16* out;
};

__device__ __align__(128) float g_po[NCHUNK * 256];
__device__ __align__(128) float g_ml[NCHUNK * 8];
__device__ __align__(128) float g_q[QW];
__device__ __align__(128) float g_fin[MAXG * DM];
__device__ unsigned g_mark[MAXG];
__device__ unsigned g_epoch;
__device__ unsigned g_ctr;

__device__ __forceinline__ uint32_t smem_u32(const void* p) { return (uint32_t)__cvta_generic_to_shared(p); }
__device__ __forceinline__ void mbar_init(uint32_t bar, int cnt) {
    asm volatile("mbarrier.init.shared::cta.b64 [%0], %1;" ::"r"(bar), "r"(cnt) : "memory");
}
__device__ __forceinline__ void mbar_expect_tx(uint32_t bar, uint32_t bytes) {
    asm volatile("mbarrier.arrive.expect_tx.shared::cta.b64 _, [%0], %1;" ::"r"(bar), "r"(bytes) : "memory");
}
__device__ __forceinline__ void mbar_arrive(uint32_t bar) {
    asm volatile("mbarrier.arrive.shared::cta.b64 _, [%0];" ::"r"(bar) : "memory");
}
__device__ __forceinline__ uint32_t clk32() { uint32_t c; asm volatile("mov.u32 %0, %clock;" : "=r"(c)); return c; }
__device__ __forceinline__ bool alive(uint32_t t0) {
    if (clk32() - t0 >= WAIT_LIMIT) __trap();
    return true;
}
__device__ __forceinline__ void mbar_wait_t(uint32_t bar, uint32_t parity, uint32_t t0) {
    uint32_t ok;
    do {
        asm volatile(
            "{\n.reg .pred p;\n"
            "mbarrier.try_wait.parity.shared::cta.b64 p, [%1], %2;\n"
            "selp.u32 %0, 1, 0, p;\n}"
            : "=r"(ok) : "r"(bar), "r"(parity) : "memory");
    } while (!ok && alive(t0));
}
__device__ __forceinline__ void tma3d(uint32_t dst, const CUtensorMap* tm, int c0, int c1, int c2, uint32_t bar, uint64_t pol) {
    asm volatile(
        "cp.async.bulk.tensor.3d.shared::cluster.global.mbarrier::complete_tx::bytes.L2::cache_hint [%0], [%1, {%3,%4,%5}], [%2], %6;"
        ::"r"(dst), "l"(tm), "r"(bar), "r"(c0), "r"(c1), "r"(c2), "l"(pol) : "memory");
}
__device__ __forceinline__ void cons_sync() { asm volatile("bar.sync 1, 256;" ::: "memory"); }
__device__ __forceinline__ void help_sync() { asm volatile("bar.sync 2, 128;" ::: "memory"); }

__device__ __forceinline__ uint32_t lds32(uint32_t a) {
    uint32_t v;
    asm volatile("ld.shared.u32 %0, [%1];" : "=r"(v) : "r"(a));
    return v;
}
__device__ __forceinline__ uint4 lds128(uint32_t a) {
    uint4 v;
    asm volatile("ld.shared.v4.u32 {%0,%1,%2,%3}, [%4];" : "=r"(v.x), "=r"(v.y), "=r"(v.z), "=r"(v.w) : "r"(a));
    return v;
}
__device__ __forceinline__ void ldsm4(uint32_t* r, uint32_t a) {
    asm volatile("ldmatrix.sync.aligned.m8n8.x4.shared.b16 {%0,%1,%2,%3}, [%4];"
                 : "=r"(r[0]), "=r"(r[1]), "=r"(r[2]), "=r"(r[3]) : "r"(a));
}
__device__ __forceinline__ void ldsm4t(uint32_t* r, uint32_t a) {
    asm volatile("ldmatrix.sync.aligned.m8n8.x4.trans.shared.b16 {%0,%1,%2,%3}, [%4];"
                 : "=r"(r[0]), "=r"(r[1]), "=r"(r[2]), "=r"(r[3]) : "r"(a));
}
__device__ __forceinline__ void mma16816(float* c, const uint32_t* a, uint32_t b0, uint32_t b1) {
    asm volatile(
        "mma.sync.aligned.m16n8k16.row.col.f32.bf16.bf16.f32 {%0,%1,%2,%3}, {%4,%5,%6,%7}, {%8,%9}, {%0,%1,%2,%3};"
        : "+f"(c[0]), "+f"(c[1]), "+f"(c[2]), "+f"(c[3])
        : "r"(a[0]), "r"(a[1]), "r"(a[2]), "r"(a[3]), "r"(b0), "r"(b1));
}
__device__ __forceinline__ uint4 ld_rlx4(const void* p) {
    uint4 v;
    asm volatile("ld.relaxed.gpu.global.v4.u32 {%0,%1,%2,%3}, [%4];"
                 : "=r"(v.x), "=r"(v.y), "=r"(v.z), "=r"(v.w) : "l"(p) : "memory");
    return v;
}
__device__ __forceinline__ uint2 ld_rlx2(const void* p) {
    uint2 v;
    asm volatile("ld.relaxed.gpu.global.v2.u32 {%0,%1}, [%2];" : "=r"(v.x), "=r"(v.y) : "l"(p) : "memory");
    return v;
}
__device__ __forceinline__ uint32_t ld_rlx1(const void* p) {
    uint32_t v;
    asm volatile("ld.relaxed.gpu.global.u32 %0, [%1];" : "=r"(v) : "l"(p) : "memory");
    return v;
}
__device__ __forceinline__ void st_rlx1(void* p, uint32_t v) {
    asm volatile("st.relaxed.gpu.global.u32 [%0], %1;" ::"l"(p), "r"(v) : "memory");
}
__device__ __forceinline__ void st_rlx2(void* p, uint32_t a, uint32_t b) {
    asm volatile("st.relaxed.gpu.global.v2.u32 [%0], {%1,%2};" ::"l"(p), "r"(a), "r"(b) : "memory");
}
__device__ __forceinline__ void st_rlx4(void* p, uint4 v) {
    asm volatile("st.relaxed.gpu.global.v4.u32 [%0], {%1,%2,%3,%4};" ::"l"(p), "r"(v.x), "r"(v.y), "r"(v.z), "r"(v.w) : "memory");
}
__device__ __forceinline__ uint32_t tagf(float v, uint32_t tag) { return (__float_as_uint(v) & ~1u) | tag; }
__device__ __forceinline__ float untag(uint32_t w) { return __uint_as_float(w & ~1u); }
__device__ __forceinline__ uint32_t mis2(uint32_t a, uint32_t b, uint32_t tag) {
    uint32_t r;
    asm("lop3.b32 %0, %1, %2, %3, 0x7e;" : "=r"(r) : "r"(a), "r"(b), "r"(tag));
    return r;
}
__device__ __forceinline__ bool ok4(uint4 v, uint32_t tag) { return ((mis2(v.x, v.y, tag) | mis2(v.z, v.w, tag)) & 1u) == 0u; }
__device__ __forceinline__ bool ok2(uint2 v, uint32_t tag) { return (mis2(v.x, v.y, tag) & 1u) == 0u; }
__device__ __forceinline__ float bf16r(float v) { return __bfloat162float(__float2bfloat16_rn(v)); }
__device__ __forceinline__ float blo(uint32_t w) { return __uint_as_float(w << 16); }
__device__ __forceinline__ float bhi(uint32_t w) { return __uint_as_float(w & 0xffff0000u); }
__device__ __forceinline__ float ex2(float v) { float r; asm("ex2.approx.ftz.f32 %0, %1;" : "=f"(r) : "f"(v)); return r; }
__device__ __forceinline__ float sum8(uint4 w) {
    return ((blo(w.x) + bhi(w.x)) + (blo(w.y) + bhi(w.y))) + ((blo(w.z) + bhi(w.z)) + (blo(w.w) + bhi(w.w)));
}
__device__ __forceinline__ float sq8(uint4 w, float m) {
    float a, s = 0.f;
    a = blo(w.x) - m; s = fmaf(a, a, s); a = bhi(w.x) - m; s = fmaf(a, a, s);
    a = blo(w.y) - m; s = fmaf(a, a, s); a = bhi(w.y) - m; s = fmaf(a, a, s);
    a = blo(w.z) - m; s = fmaf(a, a, s); a = bhi(w.z) - m; s = fmaf(a, a, s);
    a = blo(w.w) - m; s = fmaf(a, a, s); a = bhi(w.w) - m; s = fmaf(a, a, s);
    return s;
}
__device__ __forceinline__ uint32_t pack_bf16(float lo, float hi) {
    return (__float_as_uint(lo) >> 16) | (__float_as_uint(hi) & 0xffff0000u);
}

constexpr float LOG2E = 1.4426950408889634f;

__global__ void __launch_bounds__(NTHREADS, 1)
fused_decode_kernel(const __grid_constant__ Params prm) {
    extern __shared__ __align__(1024) uint8_t sptr[];
    const uint32_t sbase = smem_u32(sptr);
    const int tid = threadIdx.x, warp = tid >> 5, lane = tid & 31;
    const int b = blockIdx.x, G = gridDim.x;
    const uint32_t bar_full = sbase + OFF_BAR;
    const uint32_t bar_empty = bar_full + 2 * NST * 8;
    const uint32_t bar_go = bar_empty + NST * 8, bar_o = bar_go + 8, bar_tail = bar_o + 8, bar_mark = bar_tail + 8;
    volatile int* s_item = reinterpret_cast<volatile int*>(sptr + OFF_ITEM);
    const uint32_t t0 = clk32();
    auto mbar_wait = [&](uint32_t bar, uint32_t parity) { mbar_wait_t(bar, parity, t0); };

    if (warp == 8) {
        uint64_t pol_s, pol_n;
        asm volatile("createpolicy.fractional.L2::evict_first.b64 %0, 1.0;" : "=l"(pol_s));
        asm volatile("createpolicy.fractional.L2::evict_normal.b64 %0, 1.0;" : "=l"(pol_n));
        const int u0 = 2 * G - 1 - b;
        const int pro = (G >= 128 && (b < 128 || u0 < NUNIT)) ? 2 : 0;
        int* list = reinterpret_cast<int*>(sptr + OFF_LIST);
        int npre = 0, nall = 0;
        if (lane == 0) {
            const int uf = u0 < NUNIT ? u0 : b;
#pragma unroll
            for (int i = 0; i < 4; i++) mbar_init(bar_full + i * 8, 1);
            if (pro) {
#pragma unroll
                for (int i = 0; i < 4; i++) {
                    const CUtensorMap* tm = &prm.tm[(b < 128 ? ID_WQ : ID_WG) + (i >> 1)];
                    mbar_expect_tx(bar_full + i * 8, HALF);
                    tma3d(sbase + i * HALF, tm, ((i < 2 && b < 128) ? b : uf) * 32, 0, (i & 1) * 3, bar_full + i * 8, pol_n);
                }
            }
            for (int i = 4; i < 2 * NST; i++) mbar_init(bar_full + i * 8, 1);
            for (int i = 0; i < NST; i++) mbar_init(bar_empty + i * 8, 8);
            for (int i = 0; i < 4; i++) mbar_init(bar_go + i * 8, 1);
            int n = 0;
#pragma unroll 1
            for (int t = b; t < 128; t += G) list[n++] = ID_WQ << 16 | t;
#pragma unroll 1
            for (int u = u0; u < NUNIT; u += G) {
                list[n++] = ID_WG << 16 | u; list[n++] = ID_WU << 16 | u; list[n++] = ID_WD << 16 | u;
            }
            list[n++] = ID_WG << 16 | b | F_GATHER;
            npre = n;
            const bool wo_first = G >= 128 && b < (HKV - 4) * 8;
            if (wo_first) list[n++] = ID_WO << 16 | b;
            list[n++] = ID_WU << 16 | b;
            list[n++] = ID_WD << 16 | b;
#pragma unroll 1
            for (int t = b; t < 128 && !wo_first; t += G) list[n++] = ID_WO << 16 | t;
            list[n - 1] |= F_LAST;
#pragma unroll 1
            for (int i = npre; i + 1 < n; i++) list[i] |= F_NEXT | ((list[i + 1] >> 16) & 63) << 24;
            nall = n;
            s_item[0] = list[0];
            s_item[1] = list[1];
            s_item[NST] = -1;
            asm volatile("fence.mbarrier_init.release.cluster;" ::: "memory");
        }
        __syncwarp();
        asm volatile("bar.arrive 3, %0;" ::"n"(NTHREADS) : "memory");
        if (lane == 0) {
            int s = pro; uint32_t ph = 1;
            int infl = 2 * pro;
            int lh = 0; uint32_t lph = 0;
            int li = pro;
            int c = b, nxt = 0;
            bool isv = false;
#pragma unroll 1
            while (li < nall) {
                int item, limit = (c >= NCHUNK - G) ? KH_END : KH_ATT;
                if (li == npre && c < NCHUNK) {
                    item = (isv ? ID_V << 16 : ID_K << 16) | c;
                } else {
                    item = list[li];
                    if (li >= npre) limit = KH_FILL;
                    li++;
                }
                const int id = (item >> 16) & 7, t = item & 0xffff;
                const bool col = id >= ID_WQ && id <= ID_WU;
                const int c0 = col ? t * 32 : 0;
                const int c1 = col ? 0 : (id <= ID_V ? t * CHUNK : (id == ID_WD ? t * 32 : (t >> 3) * 256 + (t & 7) * 16));
                const int d1 = col ? 0 : (id <= ID_V ? 64 : (id == ID_WD ? 16 : 128));
                const uint32_t bytes = id <= ID_V ? KV_HALF : HALF;
                mbar_wait(bar_empty + s * 8, ph);
                s_item[s] = item;
#pragma unroll 1
                for (int h = 0; h < 2; h++) {
                    while (infl >= limit) {
                        mbar_wait(bar_full + lh * 8, lph);
                        if (++lh == 2 * NST) { lh = 0; lph ^= 1; }
                        infl--;
                    }
                    infl++;
                    const uint32_t fb = bar_full + (s * 2 + h) * 8;
                    mbar_expect_tx(fb, bytes);
                    tma3d(sbase + s * STAGE_BYTES + h * HALF, &prm.tm[id], c0, c1 + h * d1, col ? 3 * h : 0, fb,
                          col ? pol_n : pol_s);
                }
                if (++s == NST) { s = 0; ph ^= 1; }
                if (id == ID_K) {
                    nxt = G + (int)atomicInc(&g_ctr, NCHUNK - 1);
                    isv = true;
                } else if (id == ID_V) {
                    if (nxt >= NCHUNK) s_item[NST] = c;
                    c = nxt;
                    isv = false;
                }
            }
            while (infl > 0) {
                mbar_wait(bar_full + lh * 8, lph);
                if (++lh == 2 * NST) { lh = 0; lph ^= 1; }
                infl--;
            }
            mbar_arrive(bar_tail);
        }
    } else {
        uint4 xa, xb, xc;
        uint32_t xmine = 0, xmine2 = 0;
        if (warp < 8) {
            const uint4* x4 = reinterpret_cast<const uint4*>(prm.x);
            xa = __ldg(x4 + lane); xb = __ldg(x4 + 32 + lane);
            xc = make_uint4(0, 0, 0, 0);
            if (lane < 8) xc = __ldg(x4 + 64 + lane);
            xmine = __ldg(reinterpret_cast<const uint32_t*>(prm.x) + tid);
            if (tid < 32) xmine2 = __ldg(reinterpret_cast<const uint32_t*>(prm.x) + 256 + tid);
        }
        const uint32_t epoch = ld_rlx1(&g_epoch);
        asm volatile("bar.sync 3, %0;" ::"n"(NTHREADS) : "memory");
        const uint32_t tag = (epoch + 1u) & 1u;
        if (warp > 8) {
            const int hw = warp - 9;
            float* cmb = reinterpret_cast<float*>(sptr + OFF_CMB);
            __nv_bfloat16* o_s = reinterpret_cast<__nv_bfloat16*>(sptr + OFF_COEF + 512);
            {
                const uint32_t inv = tag ^ 1u;
                const uint4 iv = make_uint4(inv, inv, inv, inv);
                constexpr int c_lo = (HKV - INIT_HEADS) * CH_PER_HEAD, n_o = INIT_HEADS * CH_PER_HEAD * 64;
#pragma unroll 1
                for (int i = b * 128 + (tid - 288); i < n_o + n_o / 32; i += G * 128)
                    st_rlx4(i < n_o ? g_po + c_lo * 256 + i * 4 : g_ml + c_lo * 8 + (i - n_o) * 4, iv);
            }
#pragma unroll 1
            for (int pass = 0; pass < 2; pass++) {
                const uint32_t miss = tag ^ pass;
                if (pass && b < 128) mbar_wait(bar_go, 0);
                int ti = 0;
#pragma unroll 1
                for (int t = pass ? b : 127; t < 128; t += G, ti++) {
                    const int c4 = lane & 7, ri = lane >> 3;
                    const int cr = (t >> 3) * CH_PER_HEAD + hw * 32 + ri;
                    const float* po = g_po + (size_t)cr * 256 + (t & 7) * 32 + c4 * 4;
                    const float* pm = g_ml + cr * 8 + (c4 >> 2) * 2;
                    uint4 o4[8]; uint2 ml[8];
#pragma unroll
                    for (int i = 0; i < 8; i++) { o4[i] = make_uint4(miss, tag, tag, tag); ml[i] = make_uint2(miss, tag); }
                    bool all;
                    do {
                        all = true;
#pragma unroll
                        for (int i = 0; i < 8; i++) {
                            if (!ok4(o4[i], tag)) { o4[i] = ld_rlx4(po + i * 1024); all = false; }
                            if (!ok2(ml[i], tag)) { ml[i] = ld_rlx2(pm + i * 32); all = false; }
                        }
                    } while (!all && alive(t0));
                    float mw = untag(ml[0].x);
#pragma unroll
                    for (int i = 1; i < 8; i++) mw = fmaxf(mw, untag(ml[i].x));
                    mw = fmaxf(mw, __shfl_xor_sync(~0u, mw, 8));
                    mw = fmaxf(mw, __shfl_xor_sync(~0u, mw, 16));
                    float ox = 0.f, oy = 0.f, oz = 0.f, ow = 0.f, lw = 0.f;
#pragma unroll
                    for (int i = 0; i < 8; i++) {
                        const float f = ex2((untag(ml[i].x) - mw) * LOG2E);
                        ox = fmaf(f, untag(o4[i].x), ox); oy = fmaf(f, untag(o4[i].y), oy);
                        oz = fmaf(f, untag(o4[i].z), oz); ow = fmaf(f, untag(o4[i].w), ow);
                        lw = fmaf(f, untag(ml[i].y), lw);
                    }
#pragma unroll
                    for (int o = 8; o <= 16; o <<= 1) {
                        ox += __shfl_xor_sync(~0u, ox, o); oy += __shfl_xor_sync(~0u, oy, o);
                        oz += __shfl_xor_sync(~0u, oz, o); ow += __shfl_xor_sync(~0u, ow, o);
                        lw += __shfl_xor_sync(~0u, lw, o);
                    }
                    if (ti) help_sync();
                    if (lane < 8) *reinterpret_cast<float4*>(cmb + hw * 36 + lane * 4) = make_float4(ox, oy, oz, ow);
                    if (lane == 0 || lane == 4) { cmb[hw * 36 + 32 + (lane >> 1)] = mw; cmb[hw * 36 + 33 + (lane >> 1)] = lw; }
                    help_sync();
                    if (hw == 0) {
                        const float* mlp = cmb + 32 + (lane >> 4) * 2;
                        const float M = fmaxf(fmaxf(mlp[0], mlp[36]), fmaxf(mlp[72], mlp[108]));
                        float on = 0.f, L = 0.f;
#pragma unroll
                        for (int w = 0; w < 4; w++) {
                            const float f = ex2((mlp[w * 36] - M) * LOG2E);
                            on = fmaf(f, cmb[w * 36 + lane], on);
                            L = fmaf(f, mlp[w * 36 + 1], L);
                        }
                        o_s[(ti & 1) * 32 + (lane & 16) + ((lane & 15) >> 1) + (lane & 1) * 8] = __float2bfloat16_rn(on / L);
                    }
                }
                if (hw == 0) {
                    __syncwarp();
                    if (lane == 0 && pass) mbar_arrive(bar_o);
                } else if (hw == 3) {
                    if (pass == 0) {
                        if (lane == 0) { __threadfence(); st_rlx1(&g_mark[b], tag); }
                        __nanosleep(8000);
#pragma unroll 1
                        for (int i = lane; i < G; i += 32) {
                            while (((ld_rlx1(&g_mark[i]) ^ tag) & 1u) && alive(t0)) __nanosleep(500);
                        }
                        __threadfence();
                        __syncwarp();
                        if (lane == 0) mbar_arrive(bar_mark);
                    }
                } else {
                    int k = pass ? b + (hw - 1) * G : 143;
                    if (pass && k < 144) mbar_wait(bar_tail, 0);
#pragma unroll 1
                    for (; k < 144; k += 2 * G) {
                        const float* src = &g_fin[lane * DM + k * 4];
                        uint4 w[5];
#pragma unroll
                        for (int i = 0; i < 5; i++) w[i] = make_uint4(lane + 32 * i < G ? miss : tag, tag, tag, tag);
                        bool all;
                        do {
                            all = true;
#pragma unroll
                            for (int i = 0; i < 5; i++)
                                if (!ok4(w[i], tag)) { w[i] = ld_rlx4(src + i * 32 * DM); all = false; }
                            all = __all_sync(~0u, all);
                        } while (!all && alive(t0));
                        float sx = 0.f, sy = 0.f, sz = 0.f, sw = 0.f;
#pragma unroll
                        for (int i = 0; i < 5; i++) { sx += untag(w[i].x); sy += untag(w[i].y); sz += untag(w[i].z); sw += untag(w[i].w); }
                        const bool b4 = lane & 16, b3 = lane & 8;
                        const float r0 = (b4 ? sz : sx) + __shfl_xor_sync(~0u, b4 ? sx : sz, 16);
                        const float r1 = (b4 ? sw : sy) + __shfl_xor_sync(~0u, b4 ? sy : sw, 16);
                        float r = (b3 ? r1 : r0) + __shfl_xor_sync(~0u, b3 ? r0 : r1, 8);
                        r += __shfl_xor_sync(~0u, r, 4);
                        r += __shfl_xor_sync(~0u, r, 2);
                        r += __shfl_xor_sync(~0u, r, 1);
                        const int col = k * 4 + (lane >> 3);
                        const float xv = __bfloat162float(reinterpret_cast<const __nv_bfloat16*>(sptr + OFF_X)[col]);
                        if ((lane & 7) == 0 && pass) prm.out[col] = __float2bfloat16_rn(xv + r);
                        if (k == 0 && lane == 0) st_rlx1(&g_epoch, epoch + 1u);
                    }
                }
                if (pass == 0) help_sync();
            }
        } else {
            const int g = lane >> 2, j = lane & 3;
            const int mi = lane >> 3, l7 = lane & 7;
            float* const fin_dst = &g_fin[b * DM + warp * 72 + j * 8 + g];
            {
                float s = sum8(xa) + sum8(xb) + sum8(xc);
#pragma unroll
                for (int o = 16; o; o >>= 1) s += __shfl_xor_sync(~0u, s, o);
                const float mean = s * (1.f / DM);
                float v = sq8(xa, mean) + sq8(xb, mean) + (lane < 8 ? sq8(xc, mean) : 0.f);
#pragma unroll
                for (int o = 16; o; o >>= 1) v += __shfl_xor_sync(~0u, v, o);
                const float mb = bf16r(mean);
                const float sd = bf16r(sqrtf(bf16r(bf16r(v * (1.f / DM)) + 1e-5f)));
                uint32_t* xn_s = reinterpret_cast<uint32_t*>(sptr + OFF_XN);
                xn_s[tid] = pack_bf16(bf16r(bf16r(blo(xmine) - mb) / sd), bf16r(bf16r(bhi(xmine) - mb) / sd));
                xn_s[288 + tid] = xmine;
                if (tid < 32) {
                    xn_s[256 + tid] = pack_bf16(bf16r(bf16r(blo(xmine2) - mb) / sd), bf16r(bf16r(bhi(xmine2) - mb) / sd));
                    xn_s[288 + 256 + tid] = xmine2;
                }
                cons_sync();
            }

            int s = 0; uint32_t ph = 0;
            int rb = 0;
            float acc[5][4];
#pragma unroll
            for (int i = 0; i < 5; i++) { acc[i][0] = 0.f; acc[i][1] = 0.f; acc[i][2] = 0.f; acc[i][3] = 0.f; }
            auto release = [&]() {
                __syncwarp();
                if (lane == 0) mbar_arrive(bar_empty + s * 8);
                if (++s == NST) { s = 0; ph ^= 1; }
            };
            float* wmax = reinterpret_cast<float*>(sptr + OFF_WMAX);
            float* wsum = reinterpret_cast<float*>(sptr + OFF_WSUM);
            __nv_bfloat16* p_s = reinterpret_cast<__nv_bfloat16*>(sptr + OFF_P);
            const bool bl = (g == 0) || (g == 2);
            const uint32_t k_off = (warp >> 2) * HALF + (16 * (warp & 3) + l7 + (mi & 1) * 8) * 128;
            const uint32_t k_x = ((mi >> 1) ^ l7) << 4;
            const int vchunk = 2 * warp + (mi & 1);
            const uint32_t v_off = (vchunk >> 3) * 8192 + (l7 + (mi >> 1) * 8) * 128 + (((vchunk & 7) ^ l7) << 4);
            const uint32_t q_addr = sbase + OFF_Q + ((g >> 1) * 64 + j * 16) * 4;
            const uint32_t p_addr = sbase + OFF_P + (g >> 1) * 256 + j * 64;
            int tl = b;
            while (tl + G < 128) tl += G;
            const int go_thr = ((tl >> 3) + 1) * CH_PER_HEAD + CMB_MARGIN;
            bool fired = false;
            int nwo = 0;
            float ygate = 0.f;

            bool dry = true;
            int known = ID_WD << 16 | F_LAST;
#pragma unroll 1
            while (true) {
                const bool early = ((known >> 16) & 7) >= ID_WD;
                if (!early) mbar_wait(bar_full + (s * 2 + (warp >> 2)) * 8, ph);
                int item = early ? known : s_item[s];
                known = 0;
                const int id = (item >> 16) & 7, c = item & 0xffff;
                if (id == ID_K) {
                    if (c >= (HKV - INIT_HEADS) * CH_PER_HEAD) mbar_wait(bar_mark, 0);
                    uint32_t bf[16];
                    if (bl) {
#pragma unroll
                        for (int i = 0; i < 4; i++) {
                            const uint4 v = lds128(q_addr + (c >> 7) * 512 + i * 16);
                            bf[i * 4] = v.x; bf[i * 4 + 1] = v.y; bf[i * 4 + 2] = v.z; bf[i * 4 + 3] = v.w;
                        }
                    } else {
#pragma unroll
                        for (int i = 0; i < 16; i++) bf[i] = 0u;
                    }
                    uint32_t a[8][4];
                    {
                        const uint32_t kb = sbase + s * STAGE_BYTES + k_off;
#pragma unroll
                        for (int ks = 0; ks < 8; ks++) ldsm4(a[ks], kb + (ks >> 2) * 8192 + (k_x ^ ((ks & 3) << 5)));
                    }
                    float c0[4] = {0.f, 0.f, 0.f, 0.f}, c1[4] = {0.f, 0.f, 0.f, 0.f};
#pragma unroll
                    for (int ks = 0; ks < 8; ks += 2) {
                        mma16816(c0, a[ks], bf[2 * ks], bf[2 * ks + 1]);
                        mma16816(c1, a[ks + 1], bf[2 * ks + 2], bf[2 * ks + 3]);
                    }
                    release();
                    const float sa = bf16r(bf16r(c0[0] + c1[0]) * 0.08838834764831845f);
                    const float sb = bf16r(bf16r(c0[2] + c1[2]) * 0.08838834764831845f);
                    float mx = fmaxf(sa, sb);
                    mx = fmaxf(mx, __shfl_xor_sync(~0u, mx, 4));
                    mx = fmaxf(mx, __shfl_xor_sync(~0u, mx, 8));
                    mx = fmaxf(mx, __shfl_xor_sync(~0u, mx, 16));
                    if (lane < 2) wmax[lane * 8 + warp] = mx;
                    cons_sync();
                    float m;
                    {
                        const float4 u = *reinterpret_cast<const float4*>(wmax + (j & 1) * 8);
                        const float4 v = *reinterpret_cast<const float4*>(wmax + (j & 1) * 8 + 4);
                        m = fmaxf(fmaxf(fmaxf(u.x, u.y), fmaxf(u.z, u.w)), fmaxf(fmaxf(v.x, v.y), fmaxf(v.z, v.w)));
                    }
                    const float ea = ex2((sa - m) * LOG2E), eb = ex2((sb - m) * LOG2E);
                    if (j < 2) {
                        const int pos = j * 128 + (g >> 1) * 32 + warp * 4 + (g & 1);
                        p_s[pos] = __float2bfloat16_rn(ea);
                        p_s[pos + 2] = __float2bfloat16_rn(eb);
                    }
                    float es = ea + eb;
                    es += __shfl_xor_sync(~0u, es, 4);
                    es += __shfl_xor_sync(~0u, es, 8);
                    es += __shfl_xor_sync(~0u, es, 16);
                    if (lane < 2) wsum[lane * 8 + warp] = es;
                    cons_sync();
                    if (bl) {
#pragma unroll
                        for (int i = 0; i < 4; i++) {
                            const uint4 v = lds128(p_addr + i * 16);
                            bf[i * 4] = v.x; bf[i * 4 + 1] = v.y; bf[i * 4 + 2] = v.z; bf[i * 4 + 3] = v.w;
                        }
                    }
                    if (warp == (c & 7)) {
                        const int hh = (lane >> 1) & 1;
                        const float mh = __shfl_sync(~0u, m, hh);
                        const float4 u = *reinterpret_cast<const float4*>(wsum + hh * 8);
                        const float4 v = *reinterpret_cast<const float4*>(wsum + hh * 8 + 4);
                        const float l = ((u.x + u.y) + (u.z + u.w)) + ((v.x + v.y) + (v.z + v.w));
                        if (lane < 8) st_rlx1(g_ml + c * 8 + lane, tagf((lane & 1) ? l : mh, tag));
                    }
#pragma unroll
                    for (int k = 0; k < 4; k++) { c0[k] = 0.f; c1[k] = 0.f; }
#pragma unroll
                    for (int h = 0; h < 2; h++) {
                        mbar_wait(bar_full + (s * 2 + h) * 8, ph);
                        const uint32_t vb = sbase + s * STAGE_BYTES + h * HALF + v_off;
#pragma unroll
                        for (int ks = 0; ks < 4; ks++) ldsm4t(a[ks], vb + ks * 2048);
                        mma16816(c0, a[0], bf[8 * h], bf[8 * h + 1]);
                        mma16816(c1, a[1], bf[8 * h + 2], bf[8 * h + 3]);
                        mma16816(c0, a[2], bf[8 * h + 4], bf[8 * h + 5]);
                        mma16816(c1, a[3], bf[8 * h + 6], bf[8 * h + 7]);
                    }
                    if (j < 2)
                        st_rlx2(g_po + (size_t)c * 256 + warp * 32 + j * 16 + g * 2,
                                tagf(c0[0] + c1[0], tag), tagf(c0[2] + c1[2], tag));
                    release();
                    if (tid == 0 && !fired && (c >= go_thr || c == s_item[NST])) { mbar_arrive(bar_go); fired = true; }
                    continue;
                }
                if (id >= ID_WD) {
                    if (id == ID_WO && tid == 0 && !fired) { mbar_arrive(bar_go); fired = true; }
                    uint32_t ca = sbase + OFF_COEF + warp * 64 + j * 4;
                    if (id == ID_WO) {
                        mbar_wait(bar_o, 0);
                        ca = sbase + OFF_COEF + 512 + (nwo & 1) * 64 + j * 4;
                        nwo++;
                    }
                    const uint32_t a0 = sbase + s * STAGE_BYTES + (l7 + (mi >> 1) * 8) * 128;
#pragma unroll 1
                    for (int h = 0; h < 2; h++) {
                        const uint32_t b0 = lds32(ca + h * 32), b1 = lds32(ca + h * 32 + 16);
                        if (!dry) mbar_wait(bar_full + (s * 2 + h) * 8, ph);
                        uint32_t a[5][4];
#pragma unroll
                        for (int i = 0; i < 5; i++) {
                            const int ch = warp * 9 + (i < 4 ? 2 * i + (mi & 1) : 8);
                            ldsm4t(a[i], a0 + h * HALF + (ch >> 3) * 2048 + (((ch & 7) ^ l7) << 4));
                        }
#pragma unroll
                        for (int i = 0; i < 5; i++) mma16816(acc[i], a[i], b0, b1);
                    }
                    if (item & F_LAST) {
                        const uint32_t tg = dry ? tag ^ 1u : tag;
                        const float v0 = (j & 2) ? ((j & 1) ? acc[1][2] : acc[1][0]) : ((j & 1) ? acc[0][2] : acc[0][0]);
                        const float v1 = (j & 2) ? ((j & 1) ? acc[3][2] : acc[3][0]) : ((j & 1) ? acc[2][2] : acc[2][0]);
                        st_rlx1(fin_dst, tagf(v0, tg));
                        st_rlx1(fin_dst + 32, tagf(v1, tg));
                        if (j == 0) st_rlx1(fin_dst + 64, tagf(acc[4][0], tg));
                        if (!dry) break;
                        dry = false;
#pragma unroll
                        for (int i = 0; i < 5; i++) { acc[i][0] = 0.f; acc[i][1] = 0.f; acc[i][2] = 0.f; acc[i][3] = 0.f; }
                        continue;
                    }
                    if (early) item = s_item[s];
                    release();
                } else {
                    const int kq = warp >> 1;
                    const uint32_t a0 = sbase + s * STAGE_BYTES + (kq * 144 + l7 + (mi >> 1) * 8) * 64 +
                                        ((((warp & 1) * 2 + (mi & 1)) ^ (l7 >> 1)) << 4);
                    const uint32_t xa_ = sbase + OFF_XN + (kq * 144 + 2 * j) * 2;
                    uint32_t a[9][4], xf[18];
#pragma unroll
                    for (int ks = 0; ks < 9; ks++) {
                        ldsm4t(a[ks], a0 + ks * 1024);
                        xf[2 * ks] = lds32(xa_ + ks * 32); xf[2 * ks + 1] = lds32(xa_ + ks * 32 + 16);
                    }
                    float c0[4] = {0.f, 0.f, 0.f, 0.f}, c1[4] = {0.f, 0.f, 0.f, 0.f};
#pragma unroll
                    for (int ks = 0; ks < 9; ks++) mma16816((ks & 1) ? c1 : c0, a[ks], xf[2 * ks], xf[2 * ks + 1]);
                    float* red = reinterpret_cast<float*>(sptr + OFF_RED) + rb * 128;
                    if (j < 2) red[kq * 32 + (warp & 1) * 16 + j * 8 + g] = j ? c0[2] + c1[2] : c0[0] + c1[0];
                    release();
                    rb ^= 1;
                    cons_sync();
                    const float y = bf16r((red[lane] + red[32 + lane]) + (red[64 + lane] + red[96 + lane]));
                    if (id == ID_WQ && warp == 0) st_rlx1(&g_q[c * 32 + lane], tagf(y, tag));
                    const float sg = bf16r(ygate / (1.f + __expf(-ygate)));
                    reinterpret_cast<__nv_bfloat16*>(sptr + OFF_COEF)[warp * 32 + lane] = __float2bfloat16_rn(sg * y);
                    __syncwarp();
                    if (id == ID_WG) ygate = y;
                }
                if (item & F_NEXT) known = ((item >> 24) & 63) << 16;
                if (item & F_GATHER) {
                    uint32_t* q_s = reinterpret_cast<uint32_t*>(sptr + OFF_Q);
                    uint4 w[4];
#pragma unroll
                    for (int i = 0; i < 4; i++) { w[i].x = tag ^ 1u; w[i].y = w[i].z = w[i].w = tag; }
                    bool all;
                    do {
                        all = true;
#pragma unroll
                        for (int i = 0; i < 4; i++)
                            if (!ok4(w[i], tag)) { w[i] = ld_rlx4(&g_q[(i * 256 + tid) * 4]); all = false; }
                    } while (!all && alive(t0));
#pragma unroll
                    for (int i = 0; i < 4; i++) {
                        const int idx4 = i * 256 + tid, head = idx4 >> 5, dp = (idx4 & 31) * 2;
                        const int ks = dp >> 3, r = dp & 7;
                        const int pos = head * 64 + (r & 3) * 16 + ks * 2 + (r >> 2);
                        q_s[pos] = (w[i].x >> 16) | (w[i].y & 0xffff0000u);
                        q_s[pos + 16] = (w[i].z >> 16) | (w[i].w & 0xffff0000u);
                    }
                    cons_sync();
                }
            }
        }
    }
}

typedef CUresult (*EncodeFn)(CUtensorMap*, CUtensorMapDataType, cuuint32_t, void*, const cuuint64_t*, const cuuint64_t*,
                             const cuuint32_t*, const cuuint32_t*, CUtensorMapInterleave, CUtensorMapSwizzle,
                             CUtensorMapL2promotion, CUtensorMapFloatOOBfill);

void make_map(EncodeFn enc, CUtensorMap* tm, const void* p, cuuint64_t d0, cuuint64_t d1, cuuint64_t d2,
              cuuint64_t s1, cuuint64_t s2, cuuint32_t b0, cuuint32_t b1, cuuint32_t b2, CUtensorMapSwizzle sw) {
    cuuint64_t gd[3] = {d0, d1, d2};
    cuuint64_t gs[2] = {s1, s2};
    cuuint32_t bx[3] = {b0, b1, b2};
    cuuint32_t es[3] = {1, 1, 1};
    enc(tm, CU_TENSOR_MAP_DATA_TYPE_BFLOAT16, 3, const_cast<void*>(p), gd, gs, bx, es, CU_TENSOR_MAP_INTERLEAVE_NONE,
        sw, CU_TENSOR_MAP_L2_PROMOTION_L2_256B, CU_TENSOR_MAP_FLOAT_OOB_FILL_NONE);
}

}

extern "C" void kernel_launch(void* const* d_in, const int* in_sizes, int n_in, void* d_out, int out_size) {
    (void)in_sizes; (void)n_in; (void)out_size;
    void* fn = nullptr;
    cudaDriverEntryPointQueryResult qr;
    cudaGetDriverEntryPoint("cuTensorMapEncodeTiled", &fn, cudaEnableDefault, &qr);
    EncodeFn enc = (EncodeFn)fn;
    int dev = 0, sms = 0;
    cudaGetDevice(&dev);
    cudaDeviceGetAttribute(&sms, cudaDevAttrMultiProcessorCount, dev);
    const int G = sms < MAXG ? sms : MAXG;
    cudaFuncSetAttribute(fused_decode_kernel, cudaFuncAttributeMaxDynamicSharedMemorySize, SMEM_BYTES);

    Params prm;
    make_map(enc, &prm.tm[ID_K], d_in[1], 64, (cuuint64_t)HKV * SK, 2, 256, 128, 64, 64, 2, CU_TENSOR_MAP_SWIZZLE_128B);
    make_map(enc, &prm.tm[ID_V], d_in[2], 64, (cuuint64_t)HKV * SK, 2, 256, 128, 64, 64, 2, CU_TENSOR_MAP_SWIZZLE_128B);
    make_map(enc, &prm.tm[ID_WQ], d_in[3], QW, 96, 6, QW * 2, QW * 2 * 96, 32, 96, 3, CU_TENSOR_MAP_SWIZZLE_64B);
    make_map(enc, &prm.tm[ID_WG], d_in[6], FF, 96, 6, FF * 2, FF * 2 * 96, 32, 96, 3, CU_TENSOR_MAP_SWIZZLE_64B);
    make_map(enc, &prm.tm[ID_WU], d_in[7], FF, 96, 6, FF * 2, FF * 2 * 96, 32, 96, 3, CU_TENSOR_MAP_SWIZZLE_64B);
    make_map(enc, &prm.tm[ID_WD], d_in[8], 64, FF, 9, DM * 2, 128, 64, 16, 9, CU_TENSOR_MAP_SWIZZLE_128B);
    make_map(enc, &prm.tm[ID_WO], d_in[4], 64, QW, 9, DM * 2, 128, 64, 16, 9, CU_TENSOR_MAP_SWIZZLE_128B);
    prm.x = (const __nv_bfloat16*)d_in[0];
    prm.out = (__nv_bfloat16*)d_out;
    fused_decode_kernel<<<G, NTHREADS, SMEM_BYTES>>>(prm);
}
```
